```python
import torch

def _softmax(x, axis=-1):
    return torch.softmax(x, dim=axis)

def _gelu(x):
    return torch.nn.functional.gelu(x, approximate='tanh')

def _silu(x):
    return torch.nn.functional.silu(x)

def _sigmoid(x):
    return torch.sigmoid(x)

def _layernorm(x, axis=-1, eps=1e-05):
    m = x.mean(dim=axis, keepdim=True)
    v = x.var(dim=axis, keepdim=True, unbiased=False)
    return (x - m) / torch.sqrt(v + eps)

def _scatter_add(tgt, idx, src, axis=0):
    return tgt.clone().index_add_(axis, idx, src)

def _segment_sum(src, seg, n):
    out = torch.zeros((n,) + src.shape[1:], dtype=src.dtype)
    return out.index_add_(0, seg, src)

def _pad(x, pw):
    flat = tuple((v for pair in reversed(pw) for v in pair))
    return torch.nn.functional.pad(x, flat)
kernel_name = 'recurrent_scan__sliding_block_cached__mixer_gmlp__prompt'

def setup_inputs():

    _w = lambda a: (lambda t: t.to(torch.bfloat16) if t.is_floating_point() else t)(torch.as_tensor(a))

    def _A_setup():
        B, Sq, D = (1, 2048, 1024)
        Hq, Hkv, Sk, Dh = (32, 4, 2048, 128)
        assert Hq % Hkv == 0, (Hq, Hkv)
        return {'x': _w((lambda *s: torch.randn(*s, dtype=torch.bfloat16) * 0.05)(B, Sq, D)), 'k_cache': _w((lambda *s: torch.randn(*s, dtype=torch.bfloat16) * 0.8)(B, Hkv, Sk, Dh)), 'v_cache': _w((lambda *s: torch.randn(*s, dtype=torch.bfloat16) * 0.2)(B, Hkv, Sk, Dh)), 'wq': _w((lambda *s: torch.randn(*s, dtype=torch.bfloat16) * 0.8)(D, Hq * Dh) * D ** (-0.5)), 'wo': _w((lambda *s: torch.randn(*s, dtype=torch.bfloat16) * 0.2)(Hq * Dh, D) * (Hq * Dh) ** (-0.5))}
    _A_in = _A_setup()

    def _B_setup():
        B, S, D, F = (1, 2048, 1024, 3584)
        Fh = F // 2
        return {'x': _w((lambda *s: torch.randn(*s, dtype=torch.bfloat16) * 0.05)(B, S, D)), 'w_in': _w((lambda *s: torch.randn(*s, dtype=torch.bfloat16) * 0.4)(D, 2 * Fh)), 'w_sp': _w(0.01 * (lambda *s: torch.randn(*s, dtype=torch.bfloat16) * 0.4)(S, S)), 'b_sp': _w(1.0 + 0.01 * (lambda *s: torch.randn(*s, dtype=torch.bfloat16) * 0.1)(S)), 'w_out': _w((lambda *s: torch.randn(*s, dtype=torch.bfloat16) * 0.1)(Fh, D))}
    _B_in = _B_setup()
    return {'A_x': _A_in['x'], 'A_k_cache': _A_in['k_cache'], 'A_v_cache': _A_in['v_cache'], 'A_wq': _A_in['wq'], 'A_wo': _A_in['wo'], 'B_x': _B_in['x'], 'B_w_in': _B_in['w_in'], 'B_w_sp': _B_in['w_sp'], 'B_b_sp': _B_in['b_sp'], 'B_w_out': _B_in['w_out']}

def reference(A_x, A_k_cache, A_v_cache, A_wq, A_wo, B_x, B_w_in, B_w_sp, B_b_sp, B_w_out):

    def _A_ref(x, k_cache, v_cache, wq, wo):
        B, Sq, D = x.shape
        Hq, Dh = (32, 128)
        Hkv, Sk = (k_cache.shape[1], k_cache.shape[2])
        W = min(4096, max(256, Sk // 4))
        rep = Hq // Hkv
        q = (lambda x, *d: x.permute(*d))((x @ wq).reshape(B, Sq, Hq, Dh), 0, 2, 1, 3)
        k = (lambda x, n, axis: torch.repeat_interleave(x, n, dim=axis))(k_cache[:, :, Sk - W:, :], rep, axis=1)
        v = (lambda x, n, axis: torch.repeat_interleave(x, n, dim=axis))(v_cache[:, :, Sk - W:, :], rep, axis=1)
        scores = torch.einsum('bhqd,bhkd->bhqk', q, k) * Dh ** (-0.5)
        p = _softmax(scores, axis=-1)
        o = torch.einsum('bhqk,bhkd->bhqd', p, v)
        return (lambda x, *d: x.permute(*d))(o, 0, 2, 1, 3).reshape(B, Sq, Hq * Dh) @ wo

    def _B_ref(x, w_in, w_sp, b_sp, w_out):
        B, S, D = x.shape
        F = w_in.shape[-1]
        Fh = F // 2
        z = _gelu(torch.einsum('bsd,df->bsf', x, w_in))
        z1 = z[..., :Fh].clone()
        z2 = _layernorm(z[..., Fh:], axis=-1)
        g = torch.einsum('ts,bsf->btf', w_sp, z2) + b_sp[None, :, None]
        return torch.einsum('bsf,fd->bsd', z1 * g, w_out)
    x = A_x
    xn = _layernorm(x, axis=-1)
    s = _A_ref(xn, A_k_cache, A_v_cache, A_wq, A_wo)
    g = _silu(_B_ref(xn, B_w_in, B_w_sp, B_b_sp, B_w_out))
    return x + s * g
```

```cpp
#include <cuda_runtime.h>
#include <cuda_bf16.h>
#include <cuda.h>
#include <stdint.h>
#include <string.h>

typedef __nv_bfloat16 bf16;
#define DEVI __device__ __forceinline__

constexpr int SEQ = 2048, DM = 1024, HQD = 4096, FH = 1792, SK = 2048, WIN = 512;
constexpr int NCTA = 132;
constexpr int MAXSTEPS = 10;

__device__ bf16 g_xn[SEQ * DM];
__device__ bf16 g_z2n[SEQ * FH];
__device__ bf16 g_u[SEQ * FH];
__device__ bf16 g_o[SEQ * HQD];
__device__ bf16 g_gate[SEQ * DM];
__device__ float2 g_stats[SEQ * 8];
constexpr int F_XN = 0;
constexpr int F_STAT = 16;
constexpr int F_Z2N = 144;
constexpr int F_U = 152;
constexpr int F_O = 168;
constexpr int F_GATE = 184;
constexpr int F_DONE = 248;
constexpr int NFLAGS = 256;
__device__ unsigned g_flags[NFLAGS * 8];

DEVI uint32_t smem_u32(const void* p) { return (uint32_t)__cvta_generic_to_shared(p); }
DEVI void mbar_init(uint32_t bar, uint32_t count) { asm volatile("mbarrier.init.shared::cta.b64 [%0], %1;" :: "r"(bar), "r"(count) : "memory"); }
DEVI void mbar_expect_tx(uint32_t bar, uint32_t bytes) { asm volatile("mbarrier.arrive.expect_tx.shared::cta.b64 _, [%0], %1;" :: "r"(bar), "r"(bytes) : "memory"); }
DEVI void mbar_arrive(uint32_t bar) { asm volatile("mbarrier.arrive.shared::cta.b64 _, [%0];" :: "r"(bar) : "memory"); }
DEVI bool mbar_try_wait(uint32_t bar, uint32_t parity) {
  uint32_t ok;
  asm volatile("{\n.reg .pred p;\nmbarrier.try_wait.parity.shared::cta.b64 p, [%1], %2;\nselp.u32 %0, 1, 0, p;\n}" : "=r"(ok) : "r"(bar), "r"(parity) : "memory");
  return ok != 0;
}
DEVI void mbar_wait(uint32_t bar, uint32_t parity) { while (!mbar_try_wait(bar, parity)) { } }
DEVI unsigned long long gtimer() { unsigned long long g; asm volatile("mov.u64 %0, %%globaltimer;" : "=l"(g)); return g; }
DEVI void fence_mbar_init() { asm volatile("fence.mbarrier_init.release.cluster;" ::: "memory"); }
DEVI void fence_async_smem() { asm volatile("fence.proxy.async.shared::cta;" ::: "memory"); }
DEVI void fence_async_global() { asm volatile("fence.proxy.async.global;" ::: "memory"); }
DEVI unsigned ld_acquire(const unsigned* p) { unsigned v; asm volatile("ld.acquire.gpu.global.u32 %0, [%1];" : "=r"(v) : "l"(p) : "memory"); return v; }
DEVI void red_release(unsigned* p) { asm volatile("red.release.gpu.global.add.u32 [%0], 1;" :: "l"(p) : "memory"); }
DEVI void flag_wait(int f, unsigned target) { const unsigned* p = &g_flags[f * 8]; while (ld_acquire(p) < target) __nanosleep(32); }

DEVI void tma_load_2d(uint32_t dst, const CUtensorMap* map, uint32_t bar, int c0, int c1) {
  asm volatile("cp.async.bulk.tensor.2d.shared::cluster.global.mbarrier::complete_tx::bytes [%0], [%1, {%3, %4}], [%2];"
               :: "r"(dst), "l"(map), "r"(bar), "r"(c0), "r"(c1) : "memory");
}
DEVI void tma_load_3d(uint32_t dst, const CUtensorMap* map, uint32_t bar, int c0, int c1, int c2) {
  asm volatile("cp.async.bulk.tensor.3d.shared::cluster.global.mbarrier::complete_tx::bytes [%0], [%1, {%3, %4, %5}], [%2];"
               :: "r"(dst), "l"(map), "r"(bar), "r"(c0), "r"(c1), "r"(c2) : "memory");
}
DEVI void tma_store_2d(const CUtensorMap* map, uint32_t src, int c0, int c1) {
  asm volatile("cp.async.bulk.tensor.2d.global.shared::cta.bulk_group [%0, {%2, %3}], [%1];"
               :: "l"(map), "r"(src), "r"(c0), "r"(c1) : "memory");
}
DEVI void bulk_commit() { asm volatile("cp.async.bulk.commit_group;" ::: "memory"); }
DEVI void bulk_wait_read0() { asm volatile("cp.async.bulk.wait_group.read 0;" ::: "memory"); }
DEVI void bulk_wait0() { asm volatile("cp.async.bulk.wait_group 0;" ::: "memory"); }

DEVI void wgmma_fence() { asm volatile("wgmma.fence.sync.aligned;" ::: "memory"); }
DEVI void wgmma_commit() { asm volatile("wgmma.commit_group.sync.aligned;" ::: "memory"); }
template <int N> DEVI void wgmma_wait() { asm volatile("wgmma.wait_group.sync.aligned %0;" :: "n"(N) : "memory"); }
template <int R> DEVI void reg_alloc() { asm volatile("setmaxnreg.inc.sync.aligned.u32 %0;" :: "n"(R)); }
template <int R> DEVI void reg_dealloc() { asm volatile("setmaxnreg.dec.sync.aligned.u32 %0;" :: "n"(R)); }
DEVI void bar_sync(int id, int n) { asm volatile("bar.sync %0, %1;" :: "r"(id), "r"(n) : "memory"); }
DEVI void bar_arrive(int id, int n) { asm volatile("bar.arrive %0, %1;" :: "r"(id), "r"(n) : "memory"); }

DEVI uint64_t make_desc(uint32_t addr, uint32_t lbo) {
  return (uint64_t)(((addr & 0x3FFFF) >> 4) | ((lbo >> 4) << 16)) | (0x40000040ull << 32);
}

#define ACC8(a, i) "+f"(a[i]), "+f"(a[i+1]), "+f"(a[i+2]), "+f"(a[i+3]), "+f"(a[i+4]), "+f"(a[i+5]), "+f"(a[i+6]), "+f"(a[i+7])
#define ACC32(a, i) ACC8(a, i), ACC8(a, i+8), ACC8(a, i+16), ACC8(a, i+24)
#define ACC64(a, i) ACC32(a, i), ACC32(a, i+32)
#define REGS64 "{%0,%1,%2,%3,%4,%5,%6,%7,%8,%9,%10,%11,%12,%13,%14,%15," \
    "%16,%17,%18,%19,%20,%21,%22,%23,%24,%25,%26,%27,%28,%29,%30,%31," \
    "%32,%33,%34,%35,%36,%37,%38,%39,%40,%41,%42,%43,%44,%45,%46,%47," \
    "%48,%49,%50,%51,%52,%53,%54,%55,%56,%57,%58,%59,%60,%61,%62,%63"

DEVI void wgmma_n256_ss(float (&d)[128], uint64_t da, uint64_t db, int scale_d) {
  asm volatile("{\n.reg .pred p;\nsetp.ne.b32 p, %130, 0;\n"
    "wgmma.mma_async.sync.aligned.m64n256k16.f32.bf16.bf16 " REGS64 ","
    "%64,%65,%66,%67,%68,%69,%70,%71,%72,%73,%74,%75,%76,%77,%78,%79,"
    "%80,%81,%82,%83,%84,%85,%86,%87,%88,%89,%90,%91,%92,%93,%94,%95,"
    "%96,%97,%98,%99,%100,%101,%102,%103,%104,%105,%106,%107,%108,%109,%110,%111,"
    "%112,%113,%114,%115,%116,%117,%118,%119,%120,%121,%122,%123,%124,%125,%126,%127},"
    " %128, %129, p, 1, 1, 0, 1;\n}"
    : ACC64(d, 0), ACC64(d, 64)
    : "l"(da), "l"(db), "r"(scale_d));
}
DEVI void wgmma_n128_ss(float (&d)[64], uint64_t da, uint64_t db, int scale_d) {
  asm volatile("{\n.reg .pred p;\nsetp.ne.b32 p, %66, 0;\n"
    "wgmma.mma_async.sync.aligned.m64n128k16.f32.bf16.bf16 " REGS64 "},"
    " %64, %65, p, 1, 1, 0, 1;\n}"
    : ACC64(d, 0)
    : "l"(da), "l"(db), "r"(scale_d));
}
template <int TB>
DEVI void wgmma_n128_rs(float (&d)[64], uint32_t a0, uint32_t a1, uint32_t a2, uint32_t a3, uint64_t db, int scale_d) {
  asm volatile("{\n.reg .pred p;\nsetp.ne.b32 p, %69, 0;\n"
    "wgmma.mma_async.sync.aligned.m64n128k16.f32.bf16.bf16 " REGS64 "},"
    " {%64,%65,%66,%67}, %68, p, 1, 1, %70;\n}"
    : ACC64(d, 0)
    : "r"(a0), "r"(a1), "r"(a2), "r"(a3), "l"(db), "r"(scale_d), "n"(TB));
}
template <int N> DEVI void fence_regs(float (&a)[N]) {
#pragma unroll
  for (int i = 0; i < N; i++) asm volatile("" : "+f"(a[i]) :: "memory");
}
template <int N> DEVI void fence_regs(uint32_t (&a)[N]) {
#pragma unroll
  for (int i = 0; i < N; i++) asm volatile("" : "+r"(a[i]) :: "memory");
}
DEVI uint32_t pack_bf16(float lo, float hi) { uint32_t r; asm("cvt.rn.bf16x2.f32 %0, %1, %2;" : "=r"(r) : "f"(hi), "f"(lo)); return r; }
DEVI float bf_lo(uint32_t v) { return __uint_as_float(v << 16); }
DEVI float bf_hi(uint32_t v) { return __uint_as_float(v & 0xffff0000u); }
DEVI void stsm_x4(uint32_t addr, uint32_t r0, uint32_t r1, uint32_t r2, uint32_t r3) {
  asm volatile("stmatrix.sync.aligned.m8n8.x4.shared.b16 [%0], {%1,%2,%3,%4};" :: "r"(addr), "r"(r0), "r"(r1), "r"(r2), "r"(r3) : "memory");
}
DEVI void ldsm_x4(uint32_t addr, uint32_t& r0, uint32_t& r1, uint32_t& r2, uint32_t& r3) {
  asm volatile("ldmatrix.sync.aligned.m8n8.x4.shared.b16 {%0,%1,%2,%3}, [%4];" : "=r"(r0), "=r"(r1), "=r"(r2), "=r"(r3) : "r"(addr) : "memory");
}
DEVI void sts128(uint32_t addr, uint32_t a, uint32_t b, uint32_t c, uint32_t d) {
  asm volatile("st.shared.v4.b32 [%0], {%1,%2,%3,%4};" :: "r"(addr), "r"(a), "r"(b), "r"(c), "r"(d) : "memory");
}
DEVI void lds128(uint32_t addr, uint32_t& a, uint32_t& b, uint32_t& c, uint32_t& d) {
  asm volatile("ld.shared.v4.b32 {%0,%1,%2,%3}, [%4];" : "=r"(a), "=r"(b), "=r"(c), "=r"(d) : "r"(addr) : "memory");
}
DEVI float ex2(float x) { float r; asm("ex2.approx.ftz.f32 %0, %1;" : "=f"(r) : "f"(x)); return r; }
DEVI float tanh_fast(float x) { float r; asm("tanh.approx.f32 %0, %1;" : "=f"(r) : "f"(x)); return r; }
DEVI float act(float x, float c0, float c1) {
  float t = tanh_fast(x * fmaf(c1, x * x, c0));
  float h = 0.5f * x;
  return fmaf(h, t, h);
}

enum { M_XN = 0, M_WSP, M_U, M_O, M_X, M_GATE,
       M_K, M_V,
       M_WQ, M_WIN, M_Z2N, M_WOUT, M_WO,
       M_SZ2N, M_SU, M_SO, M_SGATE, M_SOUT,
       NMAPS };
enum { T_END = 0, T_Z2, T_Z1, T_G, T_QA, T_Y, T_S };
struct Params {
  CUtensorMap maps[NMAPS];
  const bf16* x;
  const bf16* b_sp;
  uint16_t steps[NCTA][MAXSTEPS];
};

constexpr int STAGE_BYTES = 49152;
constexpr int OFF_STG = 4 * STAGE_BYTES;
constexpr int OFF_BAR = OFF_STG + 32768;
constexpr int SMEM_BYTES = OFF_BAR + 256 + 1024;
constexpr int B_FULL = 0, B_EMPTY = 32, B_FULL6 = 64, B_EMPTY6 = 112, B_DONE = 160;

enum { P_NONE = 0, P_G1, P_G2, P_G3, P_NORM, P_ST0, P_ST1, P_SIG };

template <int I0>
DEVI void act_piece(uint32_t (&pk)[64], float c0, float c1, float (&st)[4]) {
#pragma unroll
  for (int i = I0; i < I0 + 16; i++) {
    float a = act(bf_lo(pk[i]), c0, c1), b = act(bf_hi(pk[i]), c0, c1);
    pk[i] = pack_bf16(a, b);
    st[(i & 1) * 2] += a + b;
    st[(i & 1) * 2 + 1] = fmaf(a, a, fmaf(b, b, st[(i & 1) * 2 + 1]));
  }
}

__global__ void __launch_bounds__(384, 1) mega_kernel(const __grid_constant__ Params p) {
  extern __shared__ uint8_t smem_raw[];
  const uint32_t sbase = (smem_u32(smem_raw) + 1023) & ~1023u;
  const uint32_t sbar = sbase + OFF_BAR;
  const int tid = threadIdx.x, warp = tid >> 5, lane = tid & 31;
  const int cta = blockIdx.x;
  if (tid == 0) {
    for (int s = 0; s < 4; s++) { mbar_init(sbar + B_FULL + 8 * s, 1); mbar_init(sbar + B_EMPTY + 8 * s, 8); }
    for (int s = 0; s < 6; s++) { mbar_init(sbar + B_FULL6 + 8 * s, 1); mbar_init(sbar + B_EMPTY6 + 8 * s, 8); }
    mbar_init(sbar + B_DONE, 3);
    fence_mbar_init();
  }
  __syncthreads();

  if (warp >= 8) {
    reg_dealloc<40>();
    if (warp == 8 && lane == 0) {
      int s = 0; uint32_t ph = 1;
      int s6 = 0; uint32_t ph6 = 1; bool small_started = false;
      for (int si = 0; si < MAXSTEPS; si++) {
        const uint32_t sd = p.steps[cta][si];
        const int type = sd & 7, r = (sd >> 3) & 15, c = sd >> 7;
        if (type == T_END) break;
        const int row0 = r * 128;
        if (type == T_S) {
          flag_wait(F_O + r, 64);
          fence_async_global();
          for (int kb = 0; kb < 66; kb++) {
            if (!small_started && kb < 6) {
              if (kb == 0 || kb == 1 || kb == 3 || kb == 4) mbar_wait(sbar + B_EMPTY + 8 * (kb - (kb > 2)), ph);
            } else {
              mbar_wait(sbar + B_EMPTY6 + 8 * s6, ph6);
            }
            const uint32_t st = sbase + s6 * 32768, fb = sbar + B_FULL6 + 8 * s6;
            mbar_expect_tx(fb, 32768);
            if (kb < 64) {
              tma_load_2d(st, &p.maps[M_O], fb, kb * 64, row0);
              tma_load_3d(st + 16384, &p.maps[M_WO], fb, 0, kb * 64, c * 2);
            } else {
              const CUtensorMap* m = &p.maps[M_X];
              if (kb == 65) { flag_wait(F_GATE + r * 4 + (c >> 1), 2); fence_async_global(); m = &p.maps[M_GATE]; }
              tma_load_2d(st, m, fb, c * 128, row0);
              tma_load_2d(st + 16384, m, fb, c * 128 + 64, row0);
            }
            if (++s6 == 6) { s6 = 0; ph6 ^= 1; }
          }
          small_started = true;
          continue;
        }
        const CUtensorMap *ma, *mb; int nk, nb0, df; unsigned dt; bool depA = true;
        if (type == T_Z2)      { ma = &p.maps[M_XN];  mb = &p.maps[M_WIN];  nk = 16; nb0 = 28 + c * 4; df = F_XN + r; dt = 64; }
        else if (type == T_Z1) { ma = &p.maps[M_XN];  mb = &p.maps[M_WIN];  nk = 16; nb0 = c * 4;      df = F_XN + r; dt = 64; }
        else if (type == T_G)  { ma = &p.maps[M_WSP]; mb = &p.maps[M_Z2N];  nk = 32; nb0 = c * 4;      df = F_Z2N + c; dt = 32; depA = false; }
        else if (type == T_QA) { ma = &p.maps[M_XN];  mb = &p.maps[M_WQ];   nk = 16; nb0 = c * 4;      df = F_XN + r; dt = 64; }
        else                   { ma = &p.maps[M_U];   mb = &p.maps[M_WOUT]; nk = 28; nb0 = c * 4;      df = F_U + r;  dt = 14; }
        int kb = 0;
        if (ld_acquire(&g_flags[df * 8]) < dt) {
          for (int i = 0; i < 4; i++) {
            mbar_wait(sbar + B_EMPTY + 8 * i, ph);
            const uint32_t st = sbase + i * STAGE_BYTES, fb = sbar + B_FULL + 8 * i;
            mbar_expect_tx(fb, STAGE_BYTES);
            if (depA) { tma_load_3d(st + 16384, mb, fb, 0, i * 64, nb0); tma_load_3d(st + 32768, mb, fb, 0, i * 64, nb0 + 2); }
            else tma_load_2d(st, ma, fb, i * 64, row0);
          }
          flag_wait(df, dt);
          fence_async_global();
          for (int i = 0; i < 4; i++) {
            const uint32_t st = sbase + i * STAGE_BYTES, fb = sbar + B_FULL + 8 * i;
            if (!depA) { tma_load_3d(st + 16384, mb, fb, 0, i * 64, nb0); tma_load_3d(st + 32768, mb, fb, 0, i * 64, nb0 + 2); }
            else tma_load_2d(st, ma, fb, i * 64, row0);
          }
          kb = 4; ph ^= 1;
        } else {
          fence_async_global();
        }
        for (; kb < nk; kb++) {
          mbar_wait(sbar + B_EMPTY + 8 * s, ph);
          const uint32_t st = sbase + s * STAGE_BYTES, fb = sbar + B_FULL + 8 * s;
          mbar_expect_tx(fb, STAGE_BYTES);
          tma_load_2d(st, ma, fb, kb * 64, row0);
          tma_load_3d(st + 16384, mb, fb, 0, kb * 64, nb0);
          tma_load_3d(st + 32768, mb, fb, 0, kb * 64, nb0 + 2);
          if (++s == 4) { s = 0; ph ^= 1; }
        }
        if (type == T_QA) {
          const int kv0 = (c >> 2) * SK + (SK - WIN);
          for (int i = 0; i < 16; i++) {
            const bool isv = (i == 15) || (i > 0 && (i & 1) == 0);
            const int ch = (i == 15) ? 3 : (isv ? ((i - 2) >> 1) & 3 : ((i + 1) >> 1) & 3);
            mbar_wait(sbar + B_EMPTY + 8 * s, ph);
            const uint32_t st = sbase + s * STAGE_BYTES + 16384, fb = sbar + B_FULL + 8 * s;
            const CUtensorMap* m = &p.maps[isv ? M_V : M_K];
            mbar_expect_tx(fb, 32768);
            tma_load_2d(st, m, fb, 0, kv0 + ch * 128);
            tma_load_2d(st + 16384, m, fb, 64, kv0 + ch * 128);
            if (++s == 4) { s = 0; ph ^= 1; }
          }
        }
      }
      mbar_arrive(sbar + B_DONE);
    } else if (warp == 9 && lane == 0) {
      const unsigned long long t0 = gtimer();
      while (!mbar_try_wait(sbar + B_DONE, 0)) { if (gtimer() - t0 > 2000000000ull) __trap(); }
      __threadfence();
      unsigned old = atomicAdd(&g_flags[F_DONE * 8], 1u);
      if (old == NCTA - 1) {
        __threadfence();
        for (int i = 0; i < NFLAGS; i++) g_flags[i * 8] = 0;
      }
    }
  } else {
    reg_alloc<232>();
    const int wg = warp >> 2, wq = warp & 3;
    const bool elected = (tid & 127) == 0;
    const uint32_t stg = sbase + OFF_STG + wg * 16384;
    const int mrow = wq * 16 + ((lane >> 3) & 1) * 8 + (lane & 7);
    const uint32_t moff = mrow * 128, mx = (uint32_t)(((lane >> 4) ^ (lane & 7)) << 4);

    if (cta < 128) {
      const int row = cta * 16 + warp * 2;
      uint4 v[2][4];
#pragma unroll
      for (int rr = 0; rr < 2; rr++)
#pragma unroll
        for (int i = 0; i < 4; i++) v[rr][i] = __ldg((const uint4*)(p.x + (size_t)(row + rr) * DM) + i * 32 + lane);
#pragma unroll
      for (int rr = 0; rr < 2; rr++) {
        float f[32];
#pragma unroll
        for (int i = 0; i < 4; i++) {
          f[i * 8 + 0] = bf_lo(v[rr][i].x); f[i * 8 + 1] = bf_hi(v[rr][i].x); f[i * 8 + 2] = bf_lo(v[rr][i].y); f[i * 8 + 3] = bf_hi(v[rr][i].y);
          f[i * 8 + 4] = bf_lo(v[rr][i].z); f[i * 8 + 5] = bf_hi(v[rr][i].z); f[i * 8 + 6] = bf_lo(v[rr][i].w); f[i * 8 + 7] = bf_hi(v[rr][i].w);
        }
        float s = 0.f;
#pragma unroll
        for (int i = 0; i < 32; i++) s += f[i];
#pragma unroll
        for (int o = 16; o > 0; o >>= 1) s += __shfl_xor_sync(0xffffffffu, s, o);
        const float mean = s * (1.f / DM);
        float q = 0.f;
#pragma unroll
        for (int i = 0; i < 32; i++) { f[i] -= mean; q = fmaf(f[i], f[i], q); }
#pragma unroll
        for (int o = 16; o > 0; o >>= 1) q += __shfl_xor_sync(0xffffffffu, q, o);
        const float rstd = rsqrtf(q * (1.f / DM) + 1e-5f);
#pragma unroll
        for (int i = 0; i < 4; i++) {
          uint4 o4;
          o4.x = pack_bf16(f[i * 8 + 0] * rstd, f[i * 8 + 1] * rstd); o4.y = pack_bf16(f[i * 8 + 2] * rstd, f[i * 8 + 3] * rstd);
          o4.z = pack_bf16(f[i * 8 + 4] * rstd, f[i * 8 + 5] * rstd); o4.w = pack_bf16(f[i * 8 + 6] * rstd, f[i * 8 + 7] * rstd);
          ((uint4*)(g_xn + (size_t)(row + rr) * DM))[i * 32 + lane] = o4;
        }
      }
      fence_async_global();
      __threadfence();
      __syncwarp();
      if (lane == 0) red_release(&g_flags[(F_XN + (cta >> 3)) * 8]);
    }

    int s = 0; uint32_t ph = 0;
    int s6 = 0; uint32_t ph6 = 0;
    uint32_t pk[64];
#pragma unroll
    for (int i = 0; i < 64; i++) pk[i] = 0;
    int pend = P_NONE, pend_after_act = P_NONE;
    int st_map = 0, st_col = 0, st_row = 0, sig = 0, zc = 0;
    float ac0 = 0.f, ac1 = 0.f;
    float stat[4] = {0.f, 0.f, 0.f, 0.f};
    if (wg == 1) bar_arrive(3, 256);

    for (int si = 0; si < MAXSTEPS; si++) {
      const uint32_t sd = p.steps[cta][si];
      const int type = sd & 7, r = (sd >> 3) & 15, c = sd >> 7;
      const int row0 = r * 128 + wg * 64;
      const int nturns = (type == T_END || type == T_S) ? 0 : (type == T_G ? 16 : (type == T_Y ? 14 : 8));
      const bool flush = (type == T_END || type == T_S || type == T_Y);
      float acc[128];
#pragma unroll
      for (int i = 0; i < 128; i++) acc[i] = 0.f;
      int t = 0;
      while (t < nturns || (flush && pend != P_NONE)) {
        if (!(flush && pend != P_NONE)) {
          const int s1 = s + 1;
          mbar_wait(sbar + B_FULL + 8 * s, ph);
          bar_sync(3 + wg, 256);
          {
            const uint32_t st = sbase + s * STAGE_BYTES;
            const uint64_t da = make_desc(st + wg * 8192, 16), db = make_desc(st + 16384, 8192);
            wgmma_fence();
#pragma unroll
            for (int k = 0; k < 4; k++) wgmma_n256_ss(acc, da + k * 2, db + k * 128, 1);
            wgmma_commit();
          }
          mbar_wait(sbar + B_FULL + 8 * s1, ph);
          {
            const uint32_t st = sbase + s1 * STAGE_BYTES;
            const uint64_t da = make_desc(st + wg * 8192, 16), db = make_desc(st + 16384, 8192);
            wgmma_fence();
#pragma unroll
            for (int k = 0; k < 4; k++) wgmma_n256_ss(acc, da + k * 2, db + k * 128, 1);
            wgmma_commit();
          }
          bar_arrive(3 + (wg ^ 1), 256);
          wgmma_wait<1>();
          if (lane == 0) mbar_arrive(sbar + B_EMPTY + 8 * s);
          wgmma_wait<0>();
          fence_regs(acc);
          if (lane == 0) mbar_arrive(sbar + B_EMPTY + 8 * s1);
          s ^= 2; if (s == 0) ph ^= 1;
          t++;
        }
        if (pend != P_NONE) {
          if (pend == P_G1) { act_piece<16>(pk, ac0, ac1, stat); pend = P_G2; }
          else if (pend == P_G2) { act_piece<32>(pk, ac0, ac1, stat); pend = P_G3; }
          else if (pend == P_G3) {
            act_piece<48>(pk, ac0, ac1, stat);
            pend = pend_after_act;
            if (pend == P_NORM) {
#pragma unroll
              for (int i = 0; i < 4; i++) {
                stat[i] += __shfl_xor_sync(0xffffffffu, stat[i], 1);
                stat[i] += __shfl_xor_sync(0xffffffffu, stat[i], 2);
              }
              const int row = st_row + wq * 16 + (lane >> 2);
              if ((lane & 3) == 0) g_stats[row * 8 + zc] = make_float2(stat[0], stat[1]);
              if ((lane & 3) == 1) g_stats[(row + 8) * 8 + zc] = make_float2(stat[2], stat[3]);
              __threadfence();
              __syncwarp();
              if (lane == 0) red_release(&g_flags[(F_STAT + (st_row >> 4) + wq) * 8]);
            }
          } else if (pend == P_NORM) {
            flag_wait(F_STAT + (st_row >> 4) + wq, 7);
            const int row = st_row + wq * 16 + (lane >> 2);
            float sc[2], of[2];
#pragma unroll
            for (int h = 0; h < 2; h++) {
              const float4* sp = (const float4*)&g_stats[(row + 8 * h) * 8];
              float4 a = __ldcg(sp), b = __ldcg(sp + 1), d = __ldcg(sp + 2);
              float2 e = __ldcg((const float2*)(sp + 3));
              const float sum = (a.x + a.z) + (b.x + b.z) + (d.x + d.z) + e.x;
              const float sq = (a.y + a.w) + (b.y + b.w) + (d.y + d.w) + e.y;
              const float mean = sum * (1.f / FH);
              const float var = fmaxf(sq * (1.f / FH) - mean * mean, 0.f);
              sc[h] = rsqrtf(var + 1e-5f);
              of[h] = -mean * sc[h];
            }
#pragma unroll
            for (int i = 0; i < 64; i++)
              pk[i] = pack_bf16(fmaf(bf_lo(pk[i]), sc[i & 1], of[i & 1]), fmaf(bf_hi(pk[i]), sc[i & 1], of[i & 1]));
            pend = P_ST0;
          } else if (pend == P_ST0 || pend == P_ST1) {
            if (elected) bulk_wait_read0();
            bar_sync(1 + wg, 128);
            if (pend == P_ST0) {
#pragma unroll
              for (int j = 0; j < 8; j++)
                stsm_x4(stg + (j >> 2) * 8192 + moff + (mx ^ ((j & 3) << 5)), pk[4 * j], pk[4 * j + 1], pk[4 * j + 2], pk[4 * j + 3]);
            } else {
#pragma unroll
              for (int j = 0; j < 8; j++)
                stsm_x4(stg + (j >> 2) * 8192 + moff + (mx ^ ((j & 3) << 5)), pk[32 + 4 * j], pk[33 + 4 * j], pk[34 + 4 * j], pk[35 + 4 * j]);
            }
            fence_async_smem();
            bar_sync(1 + wg, 128);
            if (elected) {
              const int col = st_col + (pend == P_ST1 ? 128 : 0);
              tma_store_2d(&p.maps[st_map], stg, col, st_row);
              tma_store_2d(&p.maps[st_map], stg + 8192, col + 64, st_row);
              bulk_commit();
            }
            pend = (pend == P_ST0) ? P_ST1 : P_SIG;
          } else {
            if (elected) { bulk_wait0(); fence_async_global(); __threadfence(); red_release(&g_flags[sig * 8]); }
            pend = P_NONE;
          }
        }
      }
      if (type == T_END) break;

      if (type == T_Z2 || type == T_Z1 || type == T_Y) {
#pragma unroll
        for (int i = 0; i < 64; i++) pk[i] = pack_bf16(acc[2 * i], acc[2 * i + 1]);
        stat[0] = stat[1] = stat[2] = stat[3] = 0.f;
        ac0 = (type == T_Y) ? 0.5f : 0.7978845608f;
        ac1 = (type == T_Y) ? 0.f : 0.0356774081f;
        act_piece<0>(pk, ac0, ac1, stat);
        pend = P_G1;
        st_row = row0; st_col = c * 256; zc = c;
        if (type == T_Z2) { pend_after_act = P_NORM; st_map = M_SZ2N; sig = F_Z2N + c; }
        else if (type == T_Z1) { pend_after_act = P_NONE; }
        else { pend_after_act = P_ST0; st_map = M_SGATE; sig = F_GATE + r * 4 + c; }
      } else if (type == T_G) {
        const int row = row0 + wq * 16 + (lane >> 2);
        const float b0 = __bfloat162float(p.b_sp[row]), b1 = __bfloat162float(p.b_sp[row + 8]);
#pragma unroll
        for (int i = 0; i < 64; i++) {
          const float b = (i & 1) ? b1 : b0;
          pk[i] = pack_bf16(bf_lo(pk[i]) * (acc[2 * i] + b), bf_hi(pk[i]) * (acc[2 * i + 1] + b));
        }
        pend = P_ST0; st_map = M_SU; st_row = row0; st_col = c * 256; sig = F_U + r;
      } else if (type == T_QA) {
        uint32_t q[32];
#pragma unroll
        for (int i = 0; i < 32; i++) q[i] = pack_bf16(acc[2 * i], acc[2 * i + 1]);
        if (elected) bulk_wait_read0();
        bar_sync(1 + wg, 128);
#pragma unroll
        for (int i = 0; i < 8; i++)
          sts128(stg + i * 2048 + (tid & 127) * 16, pack_bf16(acc[64 + 8 * i], acc[65 + 8 * i]), pack_bf16(acc[66 + 8 * i], acc[67 + 8 * i]),
                 pack_bf16(acc[68 + 8 * i], acc[69 + 8 * i]), pack_bf16(acc[70 + 8 * i], acc[71 + 8 * i]));
        constexpr float CS = 0.08838834764831845f * 1.4426950408889634f;
        float sacc[64], oacc[64];
        uint32_t pp[32];
        float m0, m1, l0, l1;
#pragma unroll
        for (int i = 0; i < 64; i++) oacc[i] = 0.f;
        mbar_wait(sbar + B_FULL + 8 * s, ph);
        bar_sync(3 + wg, 256);
        {
          const uint64_t dk = make_desc(sbase + s * STAGE_BYTES + 16384, 16);
          wgmma_fence();
#pragma unroll
          for (int k = 0; k < 8; k++) wgmma_n128_rs<0>(sacc, q[4 * k], q[4 * k + 1], q[4 * k + 2], q[4 * k + 3], dk + (k >> 2) * 1024 + (k & 3) * 2, k != 0);
          wgmma_commit();
        }
        bar_arrive(3 + (wg ^ 1), 256);
        wgmma_wait<0>();
        fence_regs(sacc);
        if (lane == 0) mbar_arrive(sbar + B_EMPTY + 8 * s);
        if (++s == 4) { s = 0; ph ^= 1; }
        {
          m0 = sacc[0]; m1 = sacc[2];
#pragma unroll
          for (int i = 0; i < 16; i++) { m0 = fmaxf(m0, fmaxf(sacc[4 * i], sacc[4 * i + 1])); m1 = fmaxf(m1, fmaxf(sacc[4 * i + 2], sacc[4 * i + 3])); }
          m0 = fmaxf(m0, __shfl_xor_sync(0xffffffffu, m0, 1)); m1 = fmaxf(m1, __shfl_xor_sync(0xffffffffu, m1, 1));
          m0 = fmaxf(m0, __shfl_xor_sync(0xffffffffu, m0, 2)); m1 = fmaxf(m1, __shfl_xor_sync(0xffffffffu, m1, 2));
          const float n0 = -m0 * CS, n1 = -m1 * CS;
          l0 = 0.f; l1 = 0.f;
#pragma unroll
          for (int i = 0; i < 16; i++) {
            const float e0 = ex2(fmaf(sacc[4 * i], CS, n0)), e1 = ex2(fmaf(sacc[4 * i + 1], CS, n0));
            const float e2 = ex2(fmaf(sacc[4 * i + 2], CS, n1)), e3 = ex2(fmaf(sacc[4 * i + 3], CS, n1));
            l0 += e0 + e1; l1 += e2 + e3;
            pp[2 * i] = pack_bf16(e0, e1); pp[2 * i + 1] = pack_bf16(e2, e3);
          }
        }
#pragma unroll 1
        for (int j = 1; j < 8; j++) {
          const int sk = s; const uint32_t phk = ph;
          if (++s == 4) { s = 0; ph ^= 1; }
          const int sv = s; const uint32_t phv = ph;
          if (++s == 4) { s = 0; ph ^= 1; }
          mbar_wait(sbar + B_FULL + 8 * sk, phk);
          mbar_wait(sbar + B_FULL + 8 * sv, phv);
          bar_sync(3 + wg, 256);
          {
            const uint64_t dk = make_desc(sbase + sk * STAGE_BYTES + 16384, 16);
            const uint64_t dv = make_desc(sbase + sv * STAGE_BYTES + 16384, 16384);
            wgmma_fence();
#pragma unroll
            for (int k = 0; k < 8; k++) wgmma_n128_rs<0>(sacc, q[4 * k], q[4 * k + 1], q[4 * k + 2], q[4 * k + 3], dk + (k >> 2) * 1024 + (k & 3) * 2, k != 0);
            wgmma_commit();
#pragma unroll
            for (int k = 0; k < 8; k++) wgmma_n128_rs<1>(oacc, pp[4 * k], pp[4 * k + 1], pp[4 * k + 2], pp[4 * k + 3], dv + k * 128, 1);
            wgmma_commit();
          }
          bar_arrive(3 + (wg ^ 1), 256);
          wgmma_wait<1>();
          fence_regs(sacc);
          if (lane == 0) mbar_arrive(sbar + B_EMPTY + 8 * sk);
          if (j == 3) {
            fence_regs(q);
#pragma unroll
            for (int i = 0; i < 8; i++) lds128(stg + i * 2048 + (tid & 127) * 16, q[4 * i], q[4 * i + 1], q[4 * i + 2], q[4 * i + 3]);
          }
          const bool newhead = (j == 4);
          float x0 = newhead ? sacc[0] : m0, x1 = newhead ? sacc[2] : m1;
#pragma unroll
          for (int i = 0; i < 16; i++) { x0 = fmaxf(x0, fmaxf(sacc[4 * i], sacc[4 * i + 1])); x1 = fmaxf(x1, fmaxf(sacc[4 * i + 2], sacc[4 * i + 3])); }
          x0 = fmaxf(x0, __shfl_xor_sync(0xffffffffu, x0, 1)); x1 = fmaxf(x1, __shfl_xor_sync(0xffffffffu, x1, 1));
          x0 = fmaxf(x0, __shfl_xor_sync(0xffffffffu, x0, 2)); x1 = fmaxf(x1, __shfl_xor_sync(0xffffffffu, x1, 2));
          const float n0 = -x0 * CS, n1 = -x1 * CS;
          const float a0 = ex2(fmaf(m0, CS, n0)), a1 = ex2(fmaf(m1, CS, n1));
          m0 = x0; m1 = x1;
          float t0 = 0.f, t1 = 0.f;
#pragma unroll
          for (int i = 0; i < 16; i++) {
            sacc[4 * i] = ex2(fmaf(sacc[4 * i], CS, n0)); sacc[4 * i + 1] = ex2(fmaf(sacc[4 * i + 1], CS, n0));
            sacc[4 * i + 2] = ex2(fmaf(sacc[4 * i + 2], CS, n1)); sacc[4 * i + 3] = ex2(fmaf(sacc[4 * i + 3], CS, n1));
            t0 += sacc[4 * i] + sacc[4 * i + 1]; t1 += sacc[4 * i + 2] + sacc[4 * i + 3];
          }
          wgmma_wait<0>();
          fence_regs(oacc);
          fence_regs(pp);
          if (lane == 0) mbar_arrive(sbar + B_EMPTY + 8 * sv);
          if (newhead) {
            l0 += __shfl_xor_sync(0xffffffffu, l0, 1); l1 += __shfl_xor_sync(0xffffffffu, l1, 1);
            l0 += __shfl_xor_sync(0xffffffffu, l0, 2); l1 += __shfl_xor_sync(0xffffffffu, l1, 2);
            const float i0 = 1.f / l0, i1 = 1.f / l1;
#pragma unroll
            for (int jj = 0; jj < 8; jj++)
              stsm_x4(stg + (jj >> 2) * 8192 + moff + (mx ^ ((jj & 3) << 5)),
                      pack_bf16(oacc[8 * jj] * i0, oacc[8 * jj + 1] * i0), pack_bf16(oacc[8 * jj + 2] * i1, oacc[8 * jj + 3] * i1),
                      pack_bf16(oacc[8 * jj + 4] * i0, oacc[8 * jj + 5] * i0), pack_bf16(oacc[8 * jj + 6] * i1, oacc[8 * jj + 7] * i1));
            fence_async_smem();
            bar_sync(1 + wg, 128);
            if (elected) {
              tma_store_2d(&p.maps[M_SO], stg, c * 256, row0);
              tma_store_2d(&p.maps[M_SO], stg + 8192, c * 256 + 64, row0);
              bulk_commit();
            }
            l0 = t0; l1 = t1;
#pragma unroll
            for (int i = 0; i < 64; i++) oacc[i] = 0.f;
          } else {
            l0 = fmaf(l0, a0, t0); l1 = fmaf(l1, a1, t1);
#pragma unroll
            for (int i = 0; i < 16; i++) { oacc[4 * i] *= a0; oacc[4 * i + 1] *= a0; oacc[4 * i + 2] *= a1; oacc[4 * i + 3] *= a1; }
          }
#pragma unroll
          for (int i = 0; i < 32; i++) pp[i] = pack_bf16(sacc[2 * i], sacc[2 * i + 1]);
        }
        mbar_wait(sbar + B_FULL + 8 * s, ph);
        bar_sync(3 + wg, 256);
        {
          const uint64_t dv = make_desc(sbase + s * STAGE_BYTES + 16384, 16384);
          wgmma_fence();
#pragma unroll
          for (int k = 0; k < 8; k++) wgmma_n128_rs<1>(oacc, pp[4 * k], pp[4 * k + 1], pp[4 * k + 2], pp[4 * k + 3], dv + k * 128, 1);
          wgmma_commit();
        }
        bar_arrive(3 + (wg ^ 1), 256);
        l0 += __shfl_xor_sync(0xffffffffu, l0, 1); l1 += __shfl_xor_sync(0xffffffffu, l1, 1);
        l0 += __shfl_xor_sync(0xffffffffu, l0, 2); l1 += __shfl_xor_sync(0xffffffffu, l1, 2);
        const float i0 = 1.f / l0, i1 = 1.f / l1;
        if (elected) { bulk_wait0(); fence_async_global(); __threadfence(); red_release(&g_flags[(F_O + r) * 8]); }
        wgmma_wait<0>();
        fence_regs(oacc);
        if (lane == 0) mbar_arrive(sbar + B_EMPTY + 8 * s);
        if (++s == 4) { s = 0; ph ^= 1; }
#pragma unroll
        for (int i = 0; i < 32; i++) {
          const float f = (i & 1) ? i1 : i0;
          pk[32 + i] = pack_bf16(oacc[2 * i] * f, oacc[2 * i + 1] * f);
          pk[i] = 0;
        }
        pend = P_ST1; st_map = M_SO; st_row = row0; st_col = c * 256; sig = F_O + r;
      } else {
        float d[64];
#pragma unroll
        for (int i = 0; i < 64; i++) d[i] = 0.f;
        int ps = 0;
#pragma unroll 1
        for (int kb = 0; kb < 64; kb++) {
          mbar_wait(sbar + B_FULL6 + 8 * s6, ph6);
          const uint32_t st = sbase + s6 * 32768;
          const uint64_t da = make_desc(st + wg * 8192, 16), db = make_desc(st + 16384, 8192);
          wgmma_fence();
#pragma unroll
          for (int k = 0; k < 4; k++) wgmma_n128_ss(d, da + k * 2, db + k * 128, 1);
          wgmma_commit();
          if (kb > 0) { wgmma_wait<1>(); if (lane == 0) mbar_arrive(sbar + B_EMPTY6 + 8 * ps); }
          ps = s6;
          if (++s6 == 6) { s6 = 0; ph6 ^= 1; }
        }
        wgmma_wait<0>();
        fence_regs(d);
        if (lane == 0) mbar_arrive(sbar + B_EMPTY6 + 8 * ps);
        const int sx = s6; const uint32_t phx = ph6;
        if (++s6 == 6) { s6 = 0; ph6 ^= 1; }
        const int sg = s6; const uint32_t phg = ph6;
        if (++s6 == 6) { s6 = 0; ph6 ^= 1; }
        if (elected) bulk_wait_read0();
        mbar_wait(sbar + B_FULL6 + 8 * sx, phx);
        mbar_wait(sbar + B_FULL6 + 8 * sg, phg);
        bar_sync(1 + wg, 128);
#pragma unroll
        for (int j = 0; j < 8; j++) {
          const uint32_t off = (j >> 2) * 16384 + wg * 8192 + moff + (mx ^ ((j & 3) << 5));
          uint32_t xv[4], gv[4], o[4];
          ldsm_x4(sbase + sx * 32768 + off, xv[0], xv[1], xv[2], xv[3]);
          ldsm_x4(sbase + sg * 32768 + off, gv[0], gv[1], gv[2], gv[3]);
#pragma unroll
          for (int e = 0; e < 4; e++)
            o[e] = pack_bf16(fmaf(d[8 * j + 2 * e], bf_lo(gv[e]), bf_lo(xv[e])), fmaf(d[8 * j + 2 * e + 1], bf_hi(gv[e]), bf_hi(xv[e])));
          stsm_x4(stg + (j >> 2) * 8192 + moff + (mx ^ ((j & 3) << 5)), o[0], o[1], o[2], o[3]);
        }
        __syncwarp();
        if (lane == 0) { mbar_arrive(sbar + B_EMPTY6 + 8 * sx); mbar_arrive(sbar + B_EMPTY6 + 8 * sg); }
        fence_async_smem();
        bar_sync(1 + wg, 128);
        if (elected) {
          tma_store_2d(&p.maps[M_SOUT], stg, c * 128, row0);
          tma_store_2d(&p.maps[M_SOUT], stg + 8192, c * 128 + 64, row0);
          bulk_commit();
        }
      }
    }
    if (elected) { bulk_wait0(); mbar_arrive(sbar + B_DONE); }
  }
}

typedef CUresult (*PFN_encodeTiled)(CUtensorMap*, CUtensorMapDataType, cuuint32_t, void*, const cuuint64_t*, const cuuint64_t*,
                                    const cuuint32_t*, const cuuint32_t*, CUtensorMapInterleave, CUtensorMapSwizzle,
                                    CUtensorMapL2promotion, CUtensorMapFloatOOBfill);
static PFN_encodeTiled s_encode = nullptr;

static void map_2d(CUtensorMap* m, const void* ptr, uint64_t rows, uint64_t cols, uint32_t br) {
  cuuint64_t dims[2] = {cols, rows}; cuuint64_t strides[1] = {cols * 2};
  cuuint32_t box[2] = {64, br}; cuuint32_t es[2] = {1, 1};
  s_encode(m, CU_TENSOR_MAP_DATA_TYPE_BFLOAT16, 2, (void*)ptr, dims, strides, box, es, CU_TENSOR_MAP_INTERLEAVE_NONE,
           CU_TENSOR_MAP_SWIZZLE_128B, CU_TENSOR_MAP_L2_PROMOTION_L2_256B, CU_TENSOR_MAP_FLOAT_OOB_FILL_NONE);
}
static void map_3d(CUtensorMap* m, const void* ptr, uint64_t rows, uint64_t cols) {
  cuuint64_t dims[3] = {64, rows, cols / 64}; cuuint64_t strides[2] = {cols * 2, 128};
  cuuint32_t box[3] = {64, 64, 2}; cuuint32_t es[3] = {1, 1, 1};
  s_encode(m, CU_TENSOR_MAP_DATA_TYPE_BFLOAT16, 3, (void*)ptr, dims, strides, box, es, CU_TENSOR_MAP_INTERLEAVE_NONE,
           CU_TENSOR_MAP_SWIZZLE_128B, CU_TENSOR_MAP_L2_PROMOTION_L2_256B, CU_TENSOR_MAP_FLOAT_OOB_FILL_NONE);
}

static void build_schedule(Params& P) {
  memset(P.steps, 0, sizeof(P.steps));
  int n[NCTA] = {0};
  auto add = [&](int cta, int type, int r, int c) { P.steps[cta][n[cta]++] = (uint16_t)(type | (r << 3) | (c << 7)); };
  for (int i = 0; i < 112; i++) { int r = i / 7, c = i % 7; add(i, T_Z2, r, c); add(i, T_Z1, r, c); add(i, T_G, r, c); }
  int qa = 0;
  auto addqa = [&](int cta) { add(cta, T_QA, qa >> 4, qa & 15); qa++; };
  for (int k = 0; k < 2; k++) for (int i = 112; i < 132; i++) addqa(i);
  for (int i = 0; i < 132; i++) addqa(i);
  for (int i = 0; i < 84; i++) addqa(i);
  int y = 0;
  for (int i = 84; i < 132; i++) { add(i, T_Y, y >> 2, y & 3); y++; }
  for (int i = 116; i < 132; i++) { add(i, T_Y, y >> 2, y & 3); y++; }
  int sidx = 0;
  for (int i = 84; i < 116; i++) { add(i, T_S, sidx >> 3, sidx & 7); sidx++; }
  for (int i = 0; i < 84; i++) { add(i, T_S, sidx >> 3, sidx & 7); sidx++; }
  for (int i = 116; i < 128; i++) { add(i, T_S, sidx >> 3, sidx & 7); sidx++; }
}

extern "C" void kernel_launch(void* const* d_in, const int* in_sizes, int n_in, void* d_out, int out_size) {
  (void)in_sizes; (void)n_in; (void)out_size;
  static Params P;
  static void *xn, *z2n, *u, *o, *gate;
  if (!s_encode) {
    void* fn = nullptr; cudaDriverEntryPointQueryResult qr;
    cudaGetDriverEntryPoint("cuTensorMapEncodeTiled", &fn, cudaEnableDefault, &qr);
    s_encode = (PFN_encodeTiled)fn;
    cudaGetSymbolAddress(&xn, g_xn); cudaGetSymbolAddress(&z2n, g_z2n); cudaGetSymbolAddress(&u, g_u);
    cudaGetSymbolAddress(&o, g_o); cudaGetSymbolAddress(&gate, g_gate);
    cudaFuncSetAttribute(mega_kernel, cudaFuncAttributeMaxDynamicSharedMemorySize, SMEM_BYTES);
    build_schedule(P);
  }
  const void *x = d_in[0], *kc = d_in[1], *vc = d_in[2], *wq = d_in[3], *wo = d_in[4];
  const void *w_in = d_in[6], *w_sp = d_in[7], *b_sp = d_in[8], *w_out = d_in[9];
  map_2d(&P.maps[M_XN], xn, SEQ, DM, 128);
  map_2d(&P.maps[M_WSP], w_sp, SEQ, SEQ, 128);
  map_2d(&P.maps[M_U], u, SEQ, FH, 128);
  map_2d(&P.maps[M_O], o, SEQ, HQD, 128);
  map_2d(&P.maps[M_X], x, SEQ, DM, 128);
  map_2d(&P.maps[M_GATE], gate, SEQ, DM, 128);
  map_2d(&P.maps[M_K], kc, 4 * SK, 128, 128);
  map_2d(&P.maps[M_V], vc, 4 * SK, 128, 128);
  map_3d(&P.maps[M_WQ], wq, DM, HQD);
  map_3d(&P.maps[M_WIN], w_in, DM, 2 * FH);
  map_3d(&P.maps[M_Z2N], z2n, SEQ, FH);
  map_3d(&P.maps[M_WOUT], w_out, FH, DM);
  map_3d(&P.maps[M_WO], wo, HQD, DM);
  map_2d(&P.maps[M_SZ2N], z2n, SEQ, FH, 64);
  map_2d(&P.maps[M_SU], u, SEQ, FH, 64);
  map_2d(&P.maps[M_SO], o, SEQ, HQD, 64);
  map_2d(&P.maps[M_SGATE], gate, SEQ, DM, 64);
  map_2d(&P.maps[M_SOUT], d_out, SEQ, DM, 64);
  P.x = (const bf16*)x;
  P.b_sp = (const bf16*)b_sp;
  mega_kernel<<<NCTA, 384, SMEM_BYTES>>>(P);
}
```

```cpp
#include <cuda_runtime.h>
#include <cuda_bf16.h>
#include <cuda.h>
#include <stdint.h>
#include <string.h>

typedef __nv_bfloat16 bf16;
#define DEVI __device__ __forceinline__

constexpr int SEQ = 2048, DM = 1024, HQD = 4096, FH = 1792, SK = 2048, WIN = 512;
constexpr int NCTA = 132;
constexpr int MAXSTEPS = 9;

__device__ __align__(1024) bf16 g_xn[SEQ * DM];
__device__ __align__(1024) bf16 g_z2n[SEQ * FH];
__device__ __align__(1024) bf16 g_u[SEQ * FH];
__device__ __align__(1024) bf16 g_o[SEQ * HQD];
__device__ __align__(1024) bf16 g_y[4 * SEQ * DM];
__device__ uint4 g_stats[SEQ * 8];
__device__ uint4 g_xstat[SEQ];
__device__ float g_cs[9 * 16 * 256];
__device__ unsigned long long g_starts;
constexpr int F_XN = 0;
constexpr int F_Z2N = 16;
constexpr int F_U = 24;
constexpr int F_O = 40;
constexpr int F_Y = 72;
constexpr int F_CS = 192;
constexpr int F_SYNC = 208;
constexpr int NFLAGS = 216;
__device__ unsigned g_flags[NFLAGS * 8];

DEVI int fresh_lane() { int l; asm volatile("mov.u32 %0, %%laneid;" : "=r"(l)); return l; }
DEVI uint32_t smem_u32(const void* p) { return (uint32_t)__cvta_generic_to_shared(p); }
DEVI void mbar_init(uint32_t bar, uint32_t count) { asm volatile("mbarrier.init.shared::cta.b64 [%0], %1;" :: "r"(bar), "r"(count) : "memory"); }
DEVI void mbar_expect_tx(uint32_t bar, uint32_t bytes) { asm volatile("mbarrier.arrive.expect_tx.shared::cta.b64 _, [%0], %1;" :: "r"(bar), "r"(bytes) : "memory"); }
DEVI void mbar_arrive(uint32_t bar) { asm volatile("mbarrier.arrive.shared::cta.b64 _, [%0];" :: "r"(bar) : "memory"); }
DEVI bool mbar_try_wait(uint32_t bar, uint32_t parity) {
  uint32_t ok;
  asm volatile("{\n.reg .pred p;\nmbarrier.try_wait.parity.shared::cta.b64 p, [%1], %2;\nselp.u32 %0, 1, 0, p;\n}" : "=r"(ok) : "r"(bar), "r"(parity) : "memory");
  return ok != 0;
}
DEVI void mbar_wait(uint32_t bar, uint32_t parity) { while (!mbar_try_wait(bar, parity)) { } }
DEVI bool mbar_try_wait_long(uint32_t bar, uint32_t parity) {
  uint32_t ok;
  asm volatile("{\n.reg .pred p;\nmbarrier.try_wait.parity.shared::cta.b64 p, [%1], %2, %3;\nselp.u32 %0, 1, 0, p;\n}" : "=r"(ok) : "r"(bar), "r"(parity), "r"(1000000u) : "memory");
  return ok != 0;
}
DEVI void mbar_wait_long(uint32_t bar, uint32_t parity) { while (!mbar_try_wait_long(bar, parity)) { } }
DEVI unsigned long long gtimer() { unsigned long long g; asm volatile("mov.u64 %0, %%globaltimer;" : "=l"(g)); return g; }
DEVI void fence_mbar_init() { asm volatile("fence.mbarrier_init.release.cluster;" ::: "memory"); }
DEVI void fence_async_smem() { asm volatile("fence.proxy.async.shared::cta;" ::: "memory"); }
DEVI void fence_async_global() { asm volatile("fence.proxy.async.global;" ::: "memory"); }
DEVI unsigned ld_acquire(const unsigned* p) { unsigned v; asm volatile("ld.acquire.gpu.global.u32 %0, [%1];" : "=r"(v) : "l"(p) : "memory"); return v; }
DEVI void red_release(unsigned* p) { asm volatile("red.release.gpu.global.add.u32 [%0], 1;" :: "l"(p) : "memory"); }
DEVI bool flag_ready(int f, unsigned target) { return (int)(ld_acquire(&g_flags[f * 8]) - target) >= 0; }
DEVI void flag_wait(int f, unsigned target) { while (!flag_ready(f, target)) __nanosleep(32); }

DEVI void tma_load_2d(uint32_t dst, const CUtensorMap* map, uint32_t bar, int c0, int c1) {
  asm volatile("cp.async.bulk.tensor.2d.shared::cluster.global.mbarrier::complete_tx::bytes [%0], [%1, {%3, %4}], [%2];"
               :: "r"(dst), "l"(map), "r"(bar), "r"(c0), "r"(c1) : "memory");
}
DEVI void load_ab(uint32_t st, uint32_t bar, uint32_t bytes, const CUtensorMap* ma, const CUtensorMap* mb, int k0, int row, int nb, uint64_t pa, uint64_t pb) {
  asm volatile("{\n.reg .pred p;\nelect.sync _|p, 0xffffffff;\n"
               "@p mbarrier.arrive.expect_tx.shared::cta.b64 _, [%1], %2;\n"
               "@p cp.async.bulk.tensor.2d.shared::cluster.global.mbarrier::complete_tx::bytes.L2::cache_hint [%0], [%3, {%5, %6}], [%1], %10;\n"
               "@p cp.async.bulk.tensor.3d.shared::cluster.global.mbarrier::complete_tx::bytes.L2::cache_hint [%8], [%4, {%9, %5, %7}], [%1], %11;\n}"
               :: "r"(st), "r"(bar), "r"(bytes), "l"(ma), "l"(mb), "r"(k0), "r"(row), "r"(nb), "r"(st + 16384), "r"(0), "l"(pa), "l"(pb) : "memory");
}
DEVI void load_pair(uint32_t st, uint32_t bar, const CUtensorMap* m, int col, int row) {
  asm volatile("{\n.reg .pred p;\nelect.sync _|p, 0xffffffff;\n"
               "@p mbarrier.arrive.expect_tx.shared::cta.b64 _, [%1], 32768;\n"
               "@p cp.async.bulk.tensor.2d.shared::cluster.global.mbarrier::complete_tx::bytes [%0], [%2, {%3, %4}], [%1];\n"
               "@p cp.async.bulk.tensor.2d.shared::cluster.global.mbarrier::complete_tx::bytes [%5], [%2, {%6, %4}], [%1];\n}"
               :: "r"(st), "r"(bar), "l"(m), "r"(col), "r"(row), "r"(st + 16384), "r"(col + 64) : "memory");
}
DEVI void tma_store_2d(const CUtensorMap* map, uint32_t src, int c0, int c1) {
  asm volatile("cp.async.bulk.tensor.2d.global.shared::cta.bulk_group [%0, {%2, %3}], [%1];"
               :: "l"(map), "r"(src), "r"(c0), "r"(c1) : "memory");
}
DEVI void bulk_commit() { asm volatile("cp.async.bulk.commit_group;" ::: "memory"); }
DEVI void bulk_wait_read0() { asm volatile("cp.async.bulk.wait_group.read 0;" ::: "memory"); }
DEVI void bulk_wait0() { asm volatile("cp.async.bulk.wait_group 0;" ::: "memory"); }

DEVI void wgmma_fence() { asm volatile("wgmma.fence.sync.aligned;" ::: "memory"); }
DEVI void wgmma_commit() { asm volatile("wgmma.commit_group.sync.aligned;" ::: "memory"); }
template <int N> DEVI void wgmma_wait() { asm volatile("wgmma.wait_group.sync.aligned %0;" :: "n"(N) : "memory"); }
template <int R> DEVI void reg_alloc() { asm volatile("setmaxnreg.inc.sync.aligned.u32 %0;" :: "n"(R)); }
template <int R> DEVI void reg_dealloc() { asm volatile("setmaxnreg.dec.sync.aligned.u32 %0;" :: "n"(R)); }
DEVI void bar_sync(int id, int n) { asm volatile("bar.sync %0, %1;" :: "r"(id), "r"(n) : "memory"); }
DEVI void bar_arrive(int id, int n) { asm volatile("bar.arrive %0, %1;" :: "r"(id), "r"(n) : "memory"); }

DEVI uint64_t make_desc(uint32_t addr, uint32_t lbo) {
  return (uint64_t)(((addr & 0x3FFFF) >> 4) | ((lbo >> 4) << 16)) | (0x40000040ull << 32);
}

#define ACC8(a, i) "+f"(a[i]), "+f"(a[i+1]), "+f"(a[i+2]), "+f"(a[i+3]), "+f"(a[i+4]), "+f"(a[i+5]), "+f"(a[i+6]), "+f"(a[i+7])
#define ACC32(a, i) ACC8(a, i), ACC8(a, i+8), ACC8(a, i+16), ACC8(a, i+24)
#define ACC64(a, i) ACC32(a, i), ACC32(a, i+32)
#define REGS64 "{%0,%1,%2,%3,%4,%5,%6,%7,%8,%9,%10,%11,%12,%13,%14,%15," \
    "%16,%17,%18,%19,%20,%21,%22,%23,%24,%25,%26,%27,%28,%29,%30,%31," \
    "%32,%33,%34,%35,%36,%37,%38,%39,%40,%41,%42,%43,%44,%45,%46,%47," \
    "%48,%49,%50,%51,%52,%53,%54,%55,%56,%57,%58,%59,%60,%61,%62,%63"

DEVI void wgmma_n256_ss(float (&d)[128], uint64_t da, uint64_t db) {
  asm volatile(
    "wgmma.mma_async.sync.aligned.m64n256k16.f32.bf16.bf16 " REGS64 ","
    "%64,%65,%66,%67,%68,%69,%70,%71,%72,%73,%74,%75,%76,%77,%78,%79,"
    "%80,%81,%82,%83,%84,%85,%86,%87,%88,%89,%90,%91,%92,%93,%94,%95,"
    "%96,%97,%98,%99,%100,%101,%102,%103,%104,%105,%106,%107,%108,%109,%110,%111,"
    "%112,%113,%114,%115,%116,%117,%118,%119,%120,%121,%122,%123,%124,%125,%126,%127},"
    " %128, %129, 1, 1, 1, 0, 1;"
    : ACC64(d, 0), ACC64(d, 64)
    : "l"(da), "l"(db));
}
DEVI void wgmma_n256_rs(float (&d)[128], uint32_t a0, uint32_t a1, uint64_t db) {
  asm volatile(
    "wgmma.mma_async.sync.aligned.m64n256k16.f32.bf16.bf16 " REGS64 ","
    "%64,%65,%66,%67,%68,%69,%70,%71,%72,%73,%74,%75,%76,%77,%78,%79,"
    "%80,%81,%82,%83,%84,%85,%86,%87,%88,%89,%90,%91,%92,%93,%94,%95,"
    "%96,%97,%98,%99,%100,%101,%102,%103,%104,%105,%106,%107,%108,%109,%110,%111,"
    "%112,%113,%114,%115,%116,%117,%118,%119,%120,%121,%122,%123,%124,%125,%126,%127},"
    " {%128, %129, %130, %130}, %131, 1, 1, 1, 1;"
    : ACC64(d, 0), ACC64(d, 64)
    : "r"(a0), "r"(a1), "r"(0), "l"(db));
}
DEVI void wgmma_n128_ss(float (&d)[128], uint64_t da, uint64_t db) {
  asm volatile(
    "wgmma.mma_async.sync.aligned.m64n128k16.f32.bf16.bf16 " REGS64 "},"
    " %64, %65, 1, 1, 1, 0, 1;"
    : ACC64(d, 0)
    : "l"(da), "l"(db));
}
template <int ACC>
DEVI void wgmma_qk(float (&d)[64], uint64_t da, uint64_t db) {
  asm volatile(
    "wgmma.mma_async.sync.aligned.m64n128k16.f32.bf16.bf16 " REGS64 "},"
    " %64, %65, %66, 1, 1, 0, 0;"
    : ACC64(d, 0)
    : "l"(da), "l"(db), "n"(ACC));
}
template <int TB>
DEVI void wgmma_n128_rs(float (&d)[64], uint32_t a0, uint32_t a1, uint32_t a2, uint32_t a3, uint64_t db, int scale_d) {
  asm volatile("{\n.reg .pred p;\nsetp.ne.b32 p, %69, 0;\n"
    "wgmma.mma_async.sync.aligned.m64n128k16.f32.bf16.bf16 " REGS64 "},"
    " {%64,%65,%66,%67}, %68, p, 1, 1, %70;\n}"
    : ACC64(d, 0)
    : "r"(a0), "r"(a1), "r"(a2), "r"(a3), "l"(db), "r"(scale_d), "n"(TB));
}
template <int N> DEVI void fence_regs(float (&a)[N]) {
#pragma unroll
  for (int i = 0; i < N; i++) asm volatile("" : "+f"(a[i]) :: "memory");
}
template <int N> DEVI void fence_regs(uint32_t (&a)[N]) {
#pragma unroll
  for (int i = 0; i < N; i++) asm volatile("" : "+r"(a[i]) :: "memory");
}
DEVI uint32_t pack_bf16(float lo, float hi) { uint32_t r; asm("cvt.rn.bf16x2.f32 %0, %1, %2;" : "=r"(r) : "f"(hi), "f"(lo)); return r; }
DEVI uint32_t bf2_add(uint32_t a, uint32_t b) { uint32_t r; asm("add.rn.bf16x2 %0, %1, %2;" : "=r"(r) : "r"(a), "r"(b)); return r; }
DEVI uint32_t bf2_mul(uint32_t a, uint32_t b) { uint32_t r; asm("mul.rn.bf16x2 %0, %1, %2;" : "=r"(r) : "r"(a), "r"(b)); return r; }
DEVI uint32_t bf2_fma(uint32_t a, uint32_t b, uint32_t c) { uint32_t r; asm("fma.rn.bf16x2 %0, %1, %2, %3;" : "=r"(r) : "r"(a), "r"(b), "r"(c)); return r; }
DEVI float bf_lo(uint32_t v) { return __uint_as_float(v << 16); }
DEVI float bf_hi(uint32_t v) { return __uint_as_float(v & 0xffff0000u); }
DEVI void stsm_x4(uint32_t addr, uint32_t r0, uint32_t r1, uint32_t r2, uint32_t r3) {
  asm volatile("stmatrix.sync.aligned.m8n8.x4.shared.b16 [%0], {%1,%2,%3,%4};" :: "r"(addr), "r"(r0), "r"(r1), "r"(r2), "r"(r3) : "memory");
}
DEVI void ldsm_x4(uint32_t addr, uint32_t& r0, uint32_t& r1, uint32_t& r2, uint32_t& r3) {
  asm volatile("ldmatrix.sync.aligned.m8n8.x4.shared.b16 {%0,%1,%2,%3}, [%4];" : "=r"(r0), "=r"(r1), "=r"(r2), "=r"(r3) : "r"(addr) : "memory");
}
DEVI void sts128(uint32_t addr, uint32_t a, uint32_t b, uint32_t c, uint32_t d) {
  asm volatile("st.shared.v4.b32 [%0], {%1,%2,%3,%4};" :: "r"(addr), "r"(a), "r"(b), "r"(c), "r"(d) : "memory");
}
DEVI void lds128(uint32_t addr, uint32_t& a, uint32_t& b, uint32_t& c, uint32_t& d) {
  asm volatile("ld.shared.v4.b32 {%0,%1,%2,%3}, [%4];" : "=r"(a), "=r"(b), "=r"(c), "=r"(d) : "r"(addr) : "memory");
}
DEVI uint32_t lds32(uint32_t addr) { uint32_t v; asm volatile("ld.shared.b32 %0, [%1];" : "=r"(v) : "r"(addr) : "memory"); return v; }
DEVI void st_relaxed_v4(uint4* p, uint32_t a, uint32_t b, uint32_t c, uint32_t d) {
  asm volatile("{\n.reg .b64 x, y;\nmov.b64 x, {%1,%2};\nmov.b64 y, {%3,%4};\nst.relaxed.gpu.global.v2.b64 [%0], {x, y};\n}"
               :: "l"(p), "r"(a), "r"(b), "r"(c), "r"(d) : "memory");
}
DEVI void ld_relaxed_v4(const uint4* p, uint32_t& a, uint32_t& b, uint32_t& c, uint32_t& d) {
  asm volatile("{\n.reg .b64 x, y;\nld.relaxed.gpu.global.v2.b64 {x, y}, [%4];\nmov.b64 {%0,%1}, x;\nmov.b64 {%2,%3}, y;\n}"
               : "=r"(a), "=r"(b), "=r"(c), "=r"(d) : "l"(p) : "memory");
}
DEVI uint4 ld_relaxed_v4(const uint4* p) { uint4 v; ld_relaxed_v4(p, v.x, v.y, v.z, v.w); return v; }
DEVI float rcp_fast(float x) { float r; asm("rcp.approx.ftz.f32 %0, %1;" : "=f"(r) : "f"(x)); return r; }
DEVI float ex2(float x) { float r; asm("ex2.approx.ftz.f32 %0, %1;" : "=f"(r) : "f"(x)); return r; }
DEVI float tanh_fast(float x) { float r; asm("tanh.approx.f32 %0, %1;" : "=f"(r) : "f"(x)); return r; }
DEVI float gelu2(float x) { return fmaf(x, tanh_fast(x * fmaf(0.0356774081f, x * x, 0.7978845608f)), x); }

enum { M_XN = 0, M_WSP, M_U, M_O, M_X, M_Y, M_K, M_V,
       M_WQ, M_WIN, M_Z2N, M_WOUT,
       M_WO2,
       M_SZ2N, M_SU, M_SO, M_SY, M_SOUT, M_X64,
       NMAPS };
enum { T_END = 0, T_Z2, T_Z1, T_G, T_QA, T_Y, T_S };
struct Params {
  CUtensorMap maps[NMAPS];
  const bf16* x;
  const bf16* b_sp;
  uint32_t never;
  uint32_t steps[NCTA][MAXSTEPS];
};

constexpr int STAGE_BYTES = 49152;
constexpr int OFF_STG = 4 * STAGE_BYTES;
constexpr int OFF_BAR = OFF_STG + 32768;
constexpr int OFF_CMD = OFF_BAR + 256;
constexpr int OFF_TAG = OFF_CMD + 32;
constexpr int SMEM_BYTES = OFF_CMD + 64;
constexpr int B_FULL = 0, B_EMPTY = 32, B_FULL6 = 64, B_EMPTY6 = 112, B_DONE = 160, B_CMD = 168, B_CDONE = 184, B_TAG = 200, B_RDY = 208, B_EXT = 216;

enum { P_NONE = 0, P_A0, P_A3 = P_A0 + 3, P_STAT, P_X, P_ST2, P_ST1, P_F0, P_F1, P_F2, P_F3, P_F4, P_F5, P_F6, P_F7 };

template <int I0>
DEVI void act_piece(uint32_t (&pk)[64], float (&st)[4]) {
#pragma unroll
  for (int i = I0; i < I0 + 16; i++) {
    const float a = gelu2(bf_lo(pk[i])), b = gelu2(bf_hi(pk[i]));
    pk[i] = pk[i + 32];
    pk[i + 32] = pack_bf16(a, b);
    st[(i & 1) * 2] += a + b;
    st[(i & 1) * 2 + 1] = fmaf(a, a, fmaf(b, b, st[(i & 1) * 2 + 1]));
  }
}

constexpr float CS = 0.08838834764831845f * 1.4426950408889634f;
DEVI float quad_sum(float v) { v += __shfl_xor_sync(0xffffffffu, v, 1); return v + __shfl_xor_sync(0xffffffffu, v, 2); }
DEVI void row_max(const float (&s)[64], float& m0, float& m1) {
  float a0 = fmaxf(s[0], s[1]), a1 = fmaxf(s[2], s[3]), b0 = fmaxf(s[4], s[5]), b1 = fmaxf(s[6], s[7]);
#pragma unroll
  for (int i = 1; i < 8; i++) {
    a0 = fmaxf(a0, fmaxf(s[8 * i], s[8 * i + 1])); a1 = fmaxf(a1, fmaxf(s[8 * i + 2], s[8 * i + 3]));
    b0 = fmaxf(b0, fmaxf(s[8 * i + 4], s[8 * i + 5])); b1 = fmaxf(b1, fmaxf(s[8 * i + 6], s[8 * i + 7]));
  }
  m0 = fmaxf(a0, b0); m1 = fmaxf(a1, b1);
  m0 = fmaxf(m0, __shfl_xor_sync(0xffffffffu, m0, 1)); m1 = fmaxf(m1, __shfl_xor_sync(0xffffffffu, m1, 1));
  m0 = fmaxf(m0, __shfl_xor_sync(0xffffffffu, m0, 2)); m1 = fmaxf(m1, __shfl_xor_sync(0xffffffffu, m1, 2));
}
DEVI uint32_t mat_off(int wq) { const int lane = fresh_lane(); return (uint32_t)((wq * 16 + (lane & 15)) * 128 + (((lane >> 4) ^ (lane & 7)) << 4)); }

DEVI void norm_params(float mean, float rstd, float& pm, float& pr) {
  const uint32_t h = pack_bf16(mean, rstd);
  pm = __uint_as_float(pack_bf16(-mean, (bf_lo(h) - mean) * rstd)); pr = __uint_as_float(pack_bf16(rstd, rstd - bf_hi(h)));
}
DEVI uint32_t get_tag(uint32_t sbase) { mbar_wait(sbase + OFF_BAR + B_TAG, 0); return lds32(sbase + OFF_TAG); }

DEVI int tpc_to_pair(int t) {
  if (t < 32) return ((0x32654107u >> ((t & 7) * 4)) & 7) * 8 + (t >> 3);
  if (t < 60) return ((0x32654107u >> (((t - 32) % 7) * 4 + 4)) & 7) * 8 + 4 + (t - 32) / 7;
  return t < 62 ? 4 + t : t - 2;
}
__host__ __device__ inline uint32_t first_step(int cta) {
  return cta < 112 ? T_Z2 | ((cta / 28) * 4 + (cta & 3)) << 3 | ((cta % 28) >> 2) << 7 : (cta < 128 ? T_QA | (cta - 112) << 3 : T_QA | (cta & 3) << 5 | 1 << 7);
}

__global__ void __launch_bounds__(384, 1) mega_kernel(const __grid_constant__ Params p) {
  extern __shared__ uint8_t smem_raw[];
  constexpr uint32_t sbase = 1024;
  constexpr uint32_t sbar = sbase + OFF_BAR;
  const int tid = threadIdx.x, warp = __shfl_sync(0xffffffffu, tid >> 5, 0), lane = tid & 31;
  uint32_t smid, nsmid;
  asm volatile("mov.u32 %0, %%smid;" : "=r"(smid)); asm("mov.u32 %0, %%nsmid;" : "=r"(nsmid));
  const int cta = __shfl_sync(0xffffffffu, nsmid == NCTA ? tpc_to_pair(smid >> 1) * 2 + (smid & 1) : blockIdx.x, 0);
  constexpr uint64_t pol_stream = 0x12F0000000000000ull, pol_normal = 0x1000000000000000ull;
  if (warp == 8) {
    if (lane == 0) {
#pragma unroll
      for (int b = B_FULL; b < B_EMPTY; b += 8) mbar_init(sbar + b, 1);
      fence_mbar_init();
    }
    __syncwarp();
    {
      const uint32_t sd = first_step(cta);
      const int r = (sd >> 3) & 15;
#pragma unroll
      for (int i = 0; i < 2; i++)
        load_ab(sbase + i * STAGE_BYTES, sbar + B_FULL + 8 * i, STAGE_BYTES, &p.maps[M_X], &p.maps[cta < 112 ? M_WIN : M_WQ],
                ((r & 12) + i) * 64, r * 128, (cta < 112 ? 28 : 0) + ((sd >> 7) & 31) * 4, pol_normal, pol_normal);
    }
    if (lane == 0) {
#pragma unroll
      for (int b = B_EMPTY; b <= B_EXT; b += 8)
        mbar_init(sbar + b, b < B_FULL6 || (b >= B_EMPTY6 && b < B_DONE) || b == B_EXT ? 8 : (b == B_DONE ? 3 : (b >= B_CMD && b < B_CDONE ? 4 : 1)));
      fence_mbar_init();
    }
    __syncwarp();
    bar_arrive(1, 384);
  } else bar_sync(1, 384);

  if (warp < 8) {
    uint32_t pk[64];
    reg_alloc<232>();
    const int wg = warp >> 2, wq = warp & 3;
    const bool elected = (tid & 127) == 0;
    const uint32_t stg = sbase + OFF_STG + wg * 16384;
    uint32_t rc = 0;
    uint32_t s6 = 0, ph6 = 0;
#pragma unroll
    for (int i = 0; i < 64; i++) pk[i] = 0;
    int pend = P_F0;
    uint32_t psd = 0;
    float stat[4] = {0.f, 0.f, 0.f, 0.f};
    uint32_t cph = 1;
    auto stg_wait = [&]() { mbar_wait(sbar + B_CDONE + 8 * wg, cph); };
    auto stg_store = [&](uint32_t map, uint32_t col, uint32_t row, uint32_t flag) {
      if (map < 0xfffd) fence_async_smem();
      if (elected) sts128(sbase + OFF_CMD + wg * 16, map, col, row, flag);
      __syncwarp();
      if (lane == 0) mbar_arrive(sbar + B_CMD + 8 * wg);
      cph ^= 1;
    };
    if (wg == 1) bar_arrive(3, 256);

#pragma unroll 1
    for (int si = 0; si < MAXSTEPS; si++) {
      const uint32_t sd = p.steps[cta][si];
      const int type = sd & 7;
      const bool flush = (type == T_END) || ((sd >> 12) & 1);
      const int hold = flush ? P_F7 : ((sd >> 26) & 1 ? P_ST2 : P_NONE);
      uint32_t bias = 0;
      if (type == T_G) {
        const unsigned short* bp = (const unsigned short*)p.b_sp + ((sd >> 3) & 15) * 128 + warp * 16 + (fresh_lane() >> 2);
        bias = (uint32_t)__ldg(bp) | ((uint32_t)__ldg(bp + 8) << 16);
      }
      float acc[128];
#pragma unroll
      for (int i = 0; i < 128; i++) acc[i] = 0.f;
      int t = type == T_END ? 0 : (type == T_S ? 32 : (type == T_G ? 16 : (type == T_Y ? ((sd >> 13) & 7) * 2 : 8)));
      const int tx = type == T_S ? 24 - (cta & 15) - (cta >> 6) * 3 : -1;
      while (t > 0 || (flush && pend != P_NONE)) {
        const bool turn = pend == P_NONE || pend > hold;
        uint32_t eb = 0;
        bool rel = false;
        if (turn) {
          if (type < T_S) {
            const uint32_t fb = sbar + B_FULL + 8 * (rc & 3), ph = (rc >> 2) & 1;
            const uint32_t st = sbase + (rc & 3) * STAGE_BYTES;
            const uint64_t da = make_desc(st + wg * 8192, 16), db = make_desc(st + 16384, 8192);
            mbar_wait(fb, ph);
            bar_sync(3 + wg, 256);
            wgmma_fence();
#pragma unroll
            for (int k = 0; k < 4; k++) wgmma_n256_ss(acc, da + k * 2, db + k * 128);
            wgmma_commit();
            mbar_wait(fb + 8, ph);
            wgmma_fence();
#pragma unroll
            for (int k = 0; k < 4; k++) wgmma_n256_ss(acc, da + (STAGE_BYTES / 16 + k * 2), db + (STAGE_BYTES / 16 + k * 128));
            wgmma_commit();
            if (pend == P_F7) {
              mbar_wait(sbar + B_EXT, 0);
              wgmma_fence();
              wgmma_n256_rs(acc, __float_as_uint(stat[0]), __float_as_uint(stat[2]), make_desc(sbase + OFF_STG, 2048));
              wgmma_commit();
              pend = P_NONE;
            }
            eb = fb + (B_EMPTY - B_FULL);
            rc += 2;
          } else {
            const uint32_t fb = sbar + B_FULL6 + 8 * s6;
            const uint32_t st = sbase + s6 * 32768;
            const uint64_t da = make_desc(st + wg * 8192, 16), db = make_desc(st + 16384, 8192);
            mbar_wait(fb, ph6);
            bar_sync(3 + wg, 256);
            wgmma_fence();
#pragma unroll
            for (int k = 0; k < 4; k++) wgmma_n128_ss(acc, da + k * 2, db + k * 128);
            wgmma_commit();
            mbar_wait(fb + 8, ph6);
            wgmma_fence();
#pragma unroll
            for (int k = 0; k < 4; k++) wgmma_n128_ss(acc, da + (2048 + k * 2), db + (2048 + k * 128));
            wgmma_commit();
            eb = fb + (B_EMPTY6 - B_FULL6);
            s6 += 2; if (s6 == 6) { s6 = 0; ph6 ^= 1; }
          }
          bar_arrive(3 + (wg ^ 1), 256);
          t--;
          if (t == tx) pend = P_X;
          if ((pend == P_NONE || pend > P_A3) && (pend < P_F0 || pend > P_F1)) { wgmma_wait<1>(); if (lane == 0) mbar_arrive(eb); rel = true; }
        }
        if (pend != P_NONE) {
          const int ptype = psd & 7, pr = (psd >> 3) & 15, pc = (psd >> 7) & 31;
          const int prow = pr * 128 + wg * 64;
          if (pend <= P_A3) {
            if (pend & 1) act_piece<0>(pk, stat); else act_piece<16>(pk, stat);
            pend++;
            if (pend == P_STAT) {
              if (ptype == T_Z2) {
#pragma unroll
                for (int i = 0; i < 4; i++) stat[i] = quad_sum(stat[i]);
                const uint32_t tag = get_tag(sbase);
                const int lane = fresh_lane();
                if ((lane & 3) < 2) {
                  const bool hi = lane & 1;
                  st_relaxed_v4(&g_stats[(prow + wq * 16 + (lane >> 2) + (hi ? 8 : 0)) * 8 + pc],
                                __float_as_uint(hi ? stat[2] : stat[0]), tag, __float_as_uint(hi ? stat[3] : stat[1]), tag);
                }
              } else pend = P_NONE;
            }
          } else if (pend >= P_F0) {
            const int lane = fresh_lane();
            const int r = (sd >> 3) & 15, grp = (type == T_QA ? 7 : 0) + ((sd >> 7) & 31);
            if (pend <= P_F1) {
              bias = get_tag(sbase);
#pragma unroll 1
              for (int sl = 2 * (pend - P_F0); sl < 2 * (pend - P_F0) + 2; sl++) {
                if (sl != (r & 3) && cta < 128) continue;
                const uint32_t a = sbase + sl * STAGE_BYTES + 16384 + (warp >> 1) * 8192 + (lane >> 2) * 128 +
                                   (((((warp & 1) << 2) | (lane & 3)) ^ (lane >> 2)) << 4);
#pragma unroll
                for (int i = 0; i < 8; i++) lds128(a + i * 1024, pk[32 + 4 * i], pk[33 + 4 * i], pk[34 + 4 * i], pk[35 + 4 * i]);
#pragma unroll
                for (int e = 0; e < 4; e++) {
                  float lo = __uint_as_float(pk[2 * e]), hi = __uint_as_float(pk[2 * e + 1]);
#pragma unroll
                  for (int i = 0; i < 8; i++) { lo += bf_lo(pk[32 + 4 * i + e]); hi += bf_hi(pk[32 + 4 * i + e]); }
                  pk[2 * e] = __float_as_uint(lo); pk[2 * e + 1] = __float_as_uint(hi);
                }
              }
              if (pend == P_F1) {
                const uint4* xp = (const uint4*)(p.x + (size_t)((cta & 127) * 16 + warp * 2 + (lane >> 4)) * DM) + (lane & 15);
#pragma unroll
                for (int i = 0; i < 8; i++)
                  asm volatile("ld.global.nc.v4.b32 {%0,%1,%2,%3}, [%4];" : "=r"(pk[32 + 4 * i]), "=r"(pk[33 + 4 * i]), "=r"(pk[34 + 4 * i]), "=r"(pk[35 + 4 * i]) : "l"(xp + i * 16) : "memory");
              }
            } else if (pend == P_F2) {
              float cs[8];
#pragma unroll
              for (int e = 0; e < 8; e++) cs[e] = __uint_as_float(pk[e]);
#pragma unroll
              for (int o = 4; o > 0; o >>= 1) {
                const bool up = (lane >> 2) & o;
#pragma unroll
                for (int e = 0; e < o; e++) cs[e] = (up ? cs[e + o] : cs[e]) + __shfl_xor_sync(0xffffffffu, up ? cs[e] : cs[e + o], o * 4);
              }
#pragma unroll
              for (int i = 32; i < 64; i++) {
                const float a = bf_lo(pk[i]), b = bf_hi(pk[i]);
                stat[0] += a; stat[2] += b; stat[1] = fmaf(a, a, stat[1]); stat[3] = fmaf(b, b, stat[3]);
              }
              float* cp = &g_cs[(grp * 16 + r) * 256 + warp * 32 + (lane & 3) * 8 + (lane >> 2)];
              cp[0] = cs[0];
              if (cta >= 128) cp[256] = cp[512] = cp[768] = 0.f;
              stg_store(0xfffe, F_CS + grp, cta >= 128 ? 4 : 1, 0);
            } else if (pend == P_F3) {
              float su = stat[0] + stat[2], sq = stat[1] + stat[3];
#pragma unroll
              for (int o = 8; o > 0; o >>= 1) { su += __shfl_xor_sync(0xffffffffu, su, o); sq += __shfl_xor_sync(0xffffffffu, sq, o); }
              const float mean = su * (1.f / DM), rstd = rsqrtf(fmaxf(sq * (1.f / DM) - mean * mean, 0.f) + 1e-5f);
              if ((lane & 15) == 0 && cta < 128) st_relaxed_v4(&g_xstat[cta * 16 + warp * 2 + (lane >> 4)], __float_as_uint(mean), bias, __float_as_uint(rstd), bias);
              norm_params(mean, rstd * CS, stat[0], stat[1]);
              stat[2] = stat[0]; stat[3] = stat[1];
              if (cta < 128) pend = P_ST1 - 1;
            } else if (pend == P_F5) {
              mbar_wait(sbar + B_RDY, 0);
              const float* cp = &g_cs[grp * 16 * 256 + warp * 32 + lane];
#pragma unroll
              for (int i = 0; i < 16; i++) asm volatile("ld.global.cg.b32 %0, [%1];" : "=r"(pk[i]) : "l"(cp + i * 256) : "memory");
              const uint4* sp = &g_xstat[r * 128 + warp * 16 + (lane >> 2)];
#pragma unroll
              for (int h = 0; h < 2; h++) ld_relaxed_v4(sp + 8 * h, pk[32 + 4 * h], pk[33 + 4 * h], pk[34 + 4 * h], pk[35 + 4 * h]);
            } else if (pend == P_F6) {
              float cs = 0.f;
#pragma unroll
              for (int i = 0; i < 16; i++) cs += __uint_as_float(pk[i]);
              const uint32_t chi = pack_bf16(cs, 0.f), clo = pack_bf16(cs - bf_lo(chi), 0.f);
              const uint32_t ba = sbase + OFF_STG + (warp >> 1) * 2048 + (lane & 7) * 2, ch = ((warp & 1) << 2) | (lane >> 3);
#pragma unroll
              for (int k = 0; k < 3; k++)
                asm volatile("st.shared.b16 [%0], %1;" :: "r"(ba + k * 128 + ((ch ^ k) << 4)), "h"((unsigned short)(k == 1 ? clo : chi)) : "memory");
              fence_async_smem();
              __syncwarp();
              if (lane == 0) mbar_arrive(sbar + B_EXT);
              const uint32_t tag = bias;
              const uint4* sp = &g_xstat[r * 128 + warp * 16 + (lane >> 2)];
              uint4 a = make_uint4(pk[32], pk[33], pk[34], pk[35]), b = make_uint4(pk[36], pk[37], pk[38], pk[39]);
              while (!__all_sync(0xffffffffu, a.y == tag && a.w == tag && b.y == tag && b.w == tag)) { a = ld_relaxed_v4(sp); b = ld_relaxed_v4(sp + 8); }
              const float m0 = -__uint_as_float(a.x), m1 = -__uint_as_float(b.x);
              const uint32_t h0 = pack_bf16(m0, m0), h1 = pack_bf16(m1, m1);
              const int q = lane & 3;
              stat[0] = __uint_as_float(q == 0 ? h0 : (q == 1 ? pack_bf16(m0 - bf_lo(h0), 0.f) : 0u));
              stat[2] = __uint_as_float(q == 0 ? h1 : (q == 1 ? pack_bf16(m1 - bf_lo(h1), 0.f) : 0u));
              stat[1] = __uint_as_float(a.z); stat[3] = __uint_as_float(b.z);
            }
            pend++;
          } else if (pend == P_X) {
            stg_wait();
            stg_store(0xfffd, ((sd >> 7) & 31) * 128, ((sd >> 3) & 15) * 128 + wg * 64, 0);
            pend = P_NONE;
          } else if (pend == P_STAT) {
            const uint32_t tag = get_tag(sbase);
            const int lane = fresh_lane();
            const uint4* sp = &g_stats[(prow + wq * 16 + (lane >> 2)) * 8 + (lane & 3)];
            const bool two = (lane & 3) != 3;
            uint4 a, b, d, e;
            bool ok;
            do {
              a = ld_relaxed_v4(sp); b = ld_relaxed_v4(sp + 64);
              d = ld_relaxed_v4(sp + (two ? 4 : 0)); e = ld_relaxed_v4(sp + (two ? 68 : 64));
              ok = a.y == tag && a.w == tag && b.y == tag && b.w == tag && d.y == tag && d.w == tag && e.y == tag && e.w == tag;
            } while (!__all_sync(0xffffffffu, ok));
            stat[0] = __uint_as_float(a.x) + (two ? __uint_as_float(d.x) : 0.f); stat[1] = __uint_as_float(a.z) + (two ? __uint_as_float(d.z) : 0.f);
            stat[2] = __uint_as_float(b.x) + (two ? __uint_as_float(e.x) : 0.f); stat[3] = __uint_as_float(b.z) + (two ? __uint_as_float(e.z) : 0.f);
#pragma unroll
            for (int h = 0; h < 2; h++) {
              const float mean = quad_sum(stat[2 * h]) * (1.f / FH);
              const float var = fmaxf(quad_sum(stat[2 * h + 1]) * (1.f / FH) - mean * mean, 0.f);
              const float rs = rsqrtf(var + 4e-5f);
              norm_params(mean, rs, stat[2 * h], stat[2 * h + 1]);
            }
            pend = P_ST2;
          } else {
            const bool first = (pend == P_ST2);
            if (ptype <= T_Z2) {
              uint32_t lo[4], hi[4];
#pragma unroll
              for (int i = 0; i < 4; i++) { lo[i] = __byte_perm(__float_as_uint(stat[i]), 0, 0x1010); hi[i] = __byte_perm(__float_as_uint(stat[i]), 0, 0x3232); }
#pragma unroll
              for (int i = 32; i < 64; i++) {
                const int h = (i & 1) * 2;
                const uint32_t d = bf2_add(pk[i], lo[h]);
                pk[i] = bf2_fma(d, lo[h + 1], bf2_fma(d, hi[h + 1], hi[h]));
              }
            }
            stg_wait();
            if (ptype == 0) {
              const int lane = fresh_lane();
              uint4* op = (uint4*)(g_xn + (size_t)(cta * 16 + warp * 2 + (lane >> 4)) * DM) + (lane & 15);
#pragma unroll
              for (int j = 0; j < 8; j++) op[j * 16] = make_uint4(pk[32 + 4 * j], pk[33 + 4 * j], pk[34 + 4 * j], pk[35 + 4 * j]);
              stg_store(0xfffe, F_XN, 1, 0);
            } else {
              const uint32_t sa = stg + mat_off(wq);
#pragma unroll
              for (int j = 0; j < 8; j++) stsm_x4((sa ^ ((j & 3) << 5)) + (j >> 2) * 8192, pk[32 + 4 * j], pk[33 + 4 * j], pk[34 + 4 * j], pk[35 + 4 * j]);
              const int map = ptype == T_Z2 ? M_SZ2N : (ptype == T_G ? M_SU : M_SY);
              const int sig = first ? 0xffff : (ptype == T_Y ? F_Y + pr * 4 + pc : (ptype == T_Z2 ? F_Z2N + pc : F_U + pr));
              stg_store(map, pc * 256 + first * 128, prow + (ptype == T_Y ? ((psd >> 19) & 3) * SEQ : 0), sig);
            }
#pragma unroll
            for (int i = 0; i < 32; i++) pk[32 + i] = pk[i];
            pend = first ? P_ST1 : (ptype ? P_NONE : P_F5);
          }
        }
        wgmma_wait<0>();
        if (turn && !rel && lane == 0) mbar_arrive(eb);
        fence_regs(acc);
        if (turn && lane == 0) mbar_arrive(eb + 8);
      }
      if (type == T_END) break;
      psd = sd;
      const bool fold = si == 0;
      if (fold || type == T_Z1) {
        const float f = type == T_QA ? CS : 1.f;
        const float rs0 = fold ? stat[1] * f : 1.f / CS, rs1 = fold ? stat[3] * f : 1.f / CS;
#pragma unroll
        for (int i = 0; i < 128; i++) acc[i] *= (i & 2) ? rs1 : rs0;
      }

      if (type == T_QA) {
        const int r = (sd >> 3) & 15, c = (sd >> 7) & 31;
        float sacc[64], oacc[64];
        uint32_t pp[32];
        auto store_q = [&](int h) {
          const uint32_t qa = sbase + wg * 8192 + h * (2 * STAGE_BYTES) + mat_off(wq);
#pragma unroll
          for (int j = 0; j < 8; j++) stsm_x4((qa ^ ((j & 3) << 5)) + (j >> 2) * STAGE_BYTES, pp[4 * j], pp[4 * j + 1], pp[4 * j + 2], pp[4 * j + 3]);
          fence_async_smem();
        };
#pragma unroll
        for (int i = 0; i < 32; i++) pp[i] = pack_bf16(acc[2 * i], acc[2 * i + 1]);
        store_q(0);
        float n0 = 0.f, n1 = 0.f, l0 = 0.f, l1 = 0.f;
        auto issue_qk = [&](uint64_t dq, uint32_t slot) {
          const uint64_t dk = make_desc(sbase + slot * STAGE_BYTES + 16384, 16);
          wgmma_qk<0>(sacc, dq, dk);
#pragma unroll
          for (int k = 1; k < 8; k++) wgmma_qk<1>(sacc, dq + ((k >> 2) * (STAGE_BYTES / 16) + (k & 3) * 2), dk + ((k >> 2) * 1024 + (k & 3) * 2));
          wgmma_commit();
        };
        auto issue_pv = [&](uint32_t slot, int accumulate) {
          const uint64_t dv = make_desc(sbase + slot * STAGE_BYTES + 16384, 16384);
#pragma unroll
          for (int k = 0; k < 8; k++) wgmma_n128_rs<1>(oacc, pp[4 * k], pp[4 * k + 1], pp[4 * k + 2], pp[4 * k + 3], dv + k * 128, k ? 1 : accumulate);
          wgmma_commit();
        };
        float i0 = 0.f, i1 = 0.f;
        auto inv_sums = [&]() { i0 = 0.25f * rcp_fast(quad_sum(l0)); i1 = 0.25f * rcp_fast(quad_sum(l1)); };
        auto stage_o = [&]() {
          const uint32_t sa = stg + mat_off(wq);
#pragma unroll
          for (int i = 0; i < 8; i++)
            stsm_x4((sa ^ ((i & 3) << 5)) + (i >> 2) * 8192,
                    pack_bf16(oacc[8 * i] * i0, oacc[8 * i + 1] * i0), pack_bf16(oacc[8 * i + 2] * i1, oacc[8 * i + 3] * i1),
                    pack_bf16(oacc[8 * i + 4] * i0, oacc[8 * i + 5] * i0), pack_bf16(oacc[8 * i + 6] * i1, oacc[8 * i + 7] * i1));
        };
        const uint32_t ph0 = (rc >> 2) & 1;
        rc += 16;
        mbar_wait(sbar + B_FULL, ph0);
        bar_sync(3 + wg, 256);
        wgmma_fence();
        issue_qk(make_desc(sbase + wg * 8192, 16), 0);
        bar_arrive(3 + (wg ^ 1), 256);
        stg_wait();
#pragma unroll
        for (int i = 0; i < 32; i++) pp[i] = pack_bf16(acc[64 + 2 * i], acc[65 + 2 * i]);
        store_q(1);
#pragma unroll
        for (int i = 0; i < 64; i++) oacc[i] = 0.f;
        wgmma_wait<0>();
        bool shifted = false;
#pragma unroll 1
        for (int j = 0; j < 8; j++) {
          uint32_t ek = sbar + B_EMPTY, ev = 0;
          if (j) {
            const uint32_t sk = 3 - 2 * (j & 1), sv = (sk + 1) & 3;
            ek = sbar + B_EMPTY + 8 * sk; ev = sbar + B_EMPTY + 8 * sv;
            mbar_wait(sbar + B_FULL + 8 * sk, ph0 ^ (((j - 1) >> 1) & 1));
            bar_sync(3 + wg, 256);
            wgmma_fence();
            issue_qk(make_desc(sbase + wg * 8192 + (j >> 2) * (2 * STAGE_BYTES), 16), sk);
            mbar_wait(sbar + B_FULL + 8 * sv, ph0 ^ ((j >> 1) & 1));
            if (j == 4) inv_sums();
            if (j == 5) stg_store(M_SO, c * 256, r * 128 + wg * 64, 0xffff);
            wgmma_fence();
            issue_pv(sv, (j - 1) & 3);
            bar_arrive(3 + (wg ^ 1), 256);
            wgmma_wait<1>();
          }
          fence_regs(sacc);
          if (lane == 0) mbar_arrive(ek);
          const bool first = (j & 3) == 0;
          if (first) { shifted = false; n0 = 0.f; n1 = 0.f; l0 = 0.f; l1 = 0.f; }
          if (__builtin_expect(shifted, 0)) {
#pragma unroll
            for (int i = 0; i < 64; i++) sacc[i] += (i & 2) ? n1 : n0;
          }
          float u[4] = {0.f, 0.f, 0.f, 0.f}, e[32];
#pragma unroll
          for (int i = 0; i < 32; i++) { e[i] = ex2(sacc[i]); u[i & 3] += e[i]; }
          if (__float_as_uint(u[0] + u[3]) == p.never)
            asm volatile("st.shared.b32 [%0], %0;" :: "r"(sbase + OFF_TAG + 8) : "memory");
          wgmma_wait<0>();
          fence_regs(oacc);
          fence_regs(pp);
          if (lane == 0 && ev) mbar_arrive(ev);
#pragma unroll
          for (int i = 0; i < 16; i++) asm volatile("cvt.rn.bf16x2.f32 %0, %1, %2;" : "=r"(pp[i]) : "f"(e[2 * i + 1]), "f"(e[2 * i]) : "memory");
#pragma unroll
          for (int i = 16; i < 32; i++) {
            const float e0 = ex2(sacc[2 * i]), e1 = ex2(sacc[2 * i + 1]);
            u[(i & 1) * 2] += e0; u[(i & 1) * 2 + 1] += e1;
            pp[i] = pack_bf16(e0, e1);
          }
          float t0 = u[0] + u[1], t1 = u[2] + u[3];
          if (__builtin_expect(__any_sync(0xffffffffu, !(t0 + t1 < 4294967296.f) || (first && fminf(t0, t1) < 2.3283064e-10f)), 0)) {
            float x0, x1;
            row_max(sacc, x0, x1);
            if (!first) { x0 = fmaxf(x0, 0.f); x1 = fmaxf(x1, 0.f); }
            const float a0 = first ? 1.f : ex2(-x0), a1 = first ? 1.f : ex2(-x1);
            n0 -= x0; n1 -= x1;
            shifted = true;
            l0 *= a0; l1 *= a1;
            t0 = 0.f; t1 = 0.f;
#pragma unroll
            for (int i = 0; i < 32; i++) {
              const float x = (i & 1) ? x1 : x0, a = (i & 1) ? a1 : a0;
              oacc[2 * i] *= a; oacc[2 * i + 1] *= a;
              const float e0 = ex2(sacc[2 * i] - x), e1 = ex2(sacc[2 * i + 1] - x);
              if (i & 1) t1 += e0 + e1; else t0 += e0 + e1;
              pp[i] = pack_bf16(e0, e1);
            }
          }
          l0 += t0; l1 += t1;
          fence_regs(pp);
          if (j == 4) stage_o();
        }
        mbar_wait(sbar + B_FULL + 24, ph0 ^ 1);
        bar_sync(3 + wg, 256);
        wgmma_fence();
        issue_pv(3, 1);
        bar_arrive(3 + (wg ^ 1), 256);
        inv_sums();
        stg_wait();
        wgmma_wait<0>();
        fence_regs(oacc);
        if (lane == 0) mbar_arrive(sbar + B_EMPTY + 24);
        stage_o();
#pragma unroll
        for (int i = 0; i < 16; i++) lds128(sbase + OFF_TAG, pk[4 * i], pk[4 * i + 1], pk[4 * i + 2], pk[4 * i + 3]);
        stat[0] = stat[1] = stat[2] = stat[3] = l0;
        stg_store(M_SO, c * 256 + 128, r * 128 + wg * 64, F_O + 2 * r + ((sd >> 13) & 1));
      } else if (type == T_S) {
        const uint32_t mx = mat_off(wq);
        float y[64];
#pragma unroll
        for (int i = 0; i < 64; i++) y[i] = 0.f;
#pragma unroll 1
        for (int n = (sd >> 18) & 7; n > 0; n--) {
          const uint32_t st = sbase + s6 * 32768 + wg * 8192 + mx;
          mbar_wait(sbar + B_FULL6 + 8 * s6, ph6);
#pragma unroll
          for (int j = 0; j < 8; j++) {
            uint32_t v[4];
            ldsm_x4((st ^ ((j & 3) << 5)) + (j >> 2) * 16384, v[0], v[1], v[2], v[3]);
#pragma unroll
            for (int e = 0; e < 4; e++) { y[8 * j + 2 * e] += bf_lo(v[e]); y[8 * j + 2 * e + 1] += bf_hi(v[e]); }
          }
          if (++s6 == 6) { s6 = 0; ph6 ^= 1; }
        }
        stg_wait();
#pragma unroll
        for (int j = 0; j < 8; j++) {
          uint32_t v[4];
          ldsm_x4(((stg + mx) ^ ((j & 3) << 5)) + (j >> 2) * 8192, v[0], v[1], v[2], v[3]);
#pragma unroll
          for (int e = 0; e < 4; e++) {
            const float y0 = y[8 * j + 2 * e], y1 = y[8 * j + 2 * e + 1];
            v[e] = pack_bf16(fmaf(acc[8 * j + 2 * e], fmaf(y0, tanh_fast(0.25f * y0), y0), bf_lo(v[e])),
                             fmaf(acc[8 * j + 2 * e + 1], fmaf(y1, tanh_fast(0.25f * y1), y1), bf_hi(v[e])));
          }
          stsm_x4(((stg + mx) ^ ((j & 3) << 5)) + (j >> 2) * 8192, v[0], v[1], v[2], v[3]);
        }
        stg_store(M_SOUT, ((sd >> 7) & 31) * 128, ((sd >> 3) & 15) * 128 + wg * 64, 0xffff);
        break;
      } else if (type == T_G) {
        const uint32_t b0 = __byte_perm(bias, 0, 0x1010), b1 = __byte_perm(bias, 0, 0x3232);
#pragma unroll
        for (int i = 0; i < 64; i++)
          pk[i] = bf2_mul(pk[i], bf2_add(pack_bf16(acc[2 * i], acc[2 * i + 1]), (i & 1) ? b1 : b0));
        pend = P_ST2;
      } else {
#pragma unroll
        for (int i = 0; i < 64; i++) pk[i] = pack_bf16(acc[2 * i], acc[2 * i + 1]);
        stat[0] = stat[1] = stat[2] = stat[3] = 0.f;
        pend = (type == T_Y) ? P_ST2 : P_A0;
      }
    }
    if (cta >= 128) { stg_wait(); stg_store(0xffff, 0, 0, 0); }
  } else {
    reg_dealloc<40>();
    if (warp == 8) {
      uint32_t rc = 6;
      uint32_t s6 = 0, ph6 = 1;
      unsigned ep = 0;
#pragma unroll 1
      for (int si = 0; si < MAXSTEPS; si++) {
        const uint32_t sd = p.steps[cta][si];
        const int type = sd & 7, r = (sd >> 3) & 15, c = (sd >> 7) & 31, aux = (sd >> 13) & 31;
        if (type == T_END) break;
        const bool small = type >= T_S;
        const bool fold = si == 0;
        int ia = fold ? M_X : M_XN, ib = M_WIN, nk = 16, nb0 = c * 4, df = F_XN; unsigned dt = 256;
        if (type == T_Z2) nb0 += 28;
        if (type == T_QA) ib = M_WQ;
        if (type == T_G) { ia = M_WSP; ib = M_Z2N; nk = 32; df = F_Z2N + c; dt = 32; }
        if (type == T_Y) { ia = M_U; ib = M_WOUT; nk = (aux & 7) * 4; df = F_U + r; dt = 14; }
        if (type == T_S) { ia = M_O; ib = M_WO2; nk = 64; df = F_O + 2 * r; dt = 2 * aux; }
        if (small) nb0 = c * 2;
        const CUtensorMap *ma = &p.maps[ia], *mb = &p.maps[ib];
        int i0 = fold ? 2 : 0;
        const uint64_t pa = (sd >> 24) & 1 ? pol_stream : pol_normal, pb = (sd >> 25) & 1 ? pol_stream : pol_normal;
        if (small && lane == 0) asm volatile("red.relaxed.gpu.global.add.u32 [%0], 1;" :: "l"(&g_flags[(F_SYNC + (cta >> 4)) * 8]) : "memory");
        if (!fold && !(df == F_XN && ep)) {
          ep = get_tag(sbase);
          const bool second = small && (lane & 1);
          if (type == T_G && si == 2) {
#pragma unroll 1
            for (int i = 0; i < 4; i++) {
              mbar_wait(sbar + B_EMPTY + 8 * i, (rc >> 2) & 1);
              if (lane == 0) { mbar_expect_tx(sbar + B_FULL + 8 * i, STAGE_BYTES); tma_load_2d(sbase + i * STAGE_BYTES, ma, sbar + B_FULL + 8 * i, i * 64, r * 128); }
              __syncwarp();
            }
            i0 = 4;
          }
          while (!__all_sync(0xffffffffu, flag_ready(second ? F_SYNC + (cta >> 4) : df, (second ? 16 : dt) * ep))) __nanosleep(32);
          fence_async_global();
          if (i0) {
            if (lane < 4)
              asm volatile("cp.async.bulk.tensor.3d.shared::cluster.global.mbarrier::complete_tx::bytes [%0], [%1, {%3, %4, %5}], [%2];"
                           :: "r"(sbase + lane * STAGE_BYTES + 16384), "l"(mb), "r"(sbar + B_FULL + 8 * lane), "r"(0), "r"(lane * 64), "r"(nb0) : "memory");
            __syncwarp();
            rc += 4;
          }
        }
        if (!small) {
          const int koff = fold ? (r & 12) : (type == T_Y ? ((sd >> 16) & 7) * 4 : 0), kmask = fold ? 15 : 63;
#pragma unroll 1
          for (int i = i0; i < nk; i++, rc++) {
            const uint32_t fb = sbar + B_FULL + 8 * (rc & 3);
            mbar_wait(fb + (B_EMPTY - B_FULL), (rc >> 2) & 1);
            load_ab(sbase + (rc & 3) * STAGE_BYTES, fb, STAGE_BYTES, ma, mb, ((i + koff) & kmask) * 64, r * 128, nb0,
                    fold && i >= 8 ? pol_stream : pa, fold && i < 12 ? pol_normal : pb);
          }
          if (type == T_QA) {
#pragma unroll 1
            for (int a = 0; a < 16; a++, rc++) {
              const bool isv = (a == 15) || (a > 0 && !(a & 1));
              const int row = (c >> 2) * SK + (SK - WIN) + ((isv ? (a - 1) >> 1 : (a + 1) >> 1) & 3) * 128;
              const uint32_t fb = sbar + B_FULL + 8 * (rc & 3);
              mbar_wait(fb + (B_EMPTY - B_FULL), (rc >> 2) & 1);
              load_pair(sbase + (rc & 3) * STAGE_BYTES + 16384, fb, &p.maps[isv ? M_V : M_K], 0, row);
            }
          }
        } else {
          const int ny = (sd >> 18) & 7;
          bool y_ok = false;
#pragma unroll 1
          for (int i = 0; i < 64; i++) {
            if (i == 4 * aux) { flag_wait(df + 1, 2 * (16 - aux) * ep); fence_async_global(); }
            const uint32_t fb = sbar + B_FULL6 + 8 * s6;
            mbar_wait(i >= 6 ? fb + (B_EMPTY6 - B_FULL6) : sbar + B_EMPTY + 8 * (s6 - (s6 > 1) - (s6 > 4)), i >= 6 ? ph6 : (rc >> 2) & 1);
            load_ab(sbase + s6 * 32768, fb, 32768, ma, mb, i * 64, r * 128, nb0, pa, pb);
            if (++s6 == 6) { s6 = 0; ph6 ^= 1; }
            if (i == 59) y_ok = flag_ready(F_Y + r * 4 + (c >> 1), 2 * ny * ep);
          }
          if (!y_ok) flag_wait(F_Y + r * 4 + (c >> 1), 2 * ny * ep);
          fence_async_global();
#pragma unroll 1
          for (int i = 0; i < ny; i++) {
            const uint32_t fb = sbar + B_FULL6 + 8 * s6;
            mbar_wait(fb + (B_EMPTY6 - B_FULL6), ph6);
            load_pair(sbase + s6 * 32768, fb, &p.maps[M_Y], c * 128, r * 128 + i * SEQ);
            if (++s6 == 6) { s6 = 0; ph6 ^= 1; }
          }
        }
      }
      if (lane == 0) mbar_arrive(sbar + B_DONE);
    } else if (warp == 9) {
      if (smem_u32(smem_raw) != sbase) __trap();
      unsigned ep = 0;
      if (lane == 0) {
        ep = (unsigned)(atomicAdd(&g_starts, 1ull) / NCTA) + 1;
        sts128(sbase + OFF_TAG, ep, 0u, 0u, 0u);
        mbar_arrive(sbar + B_TAG);
      }
      const unsigned long long t0 = gtimer();
      {
#pragma unroll 1
        for (int i = 0; i < 16; i++) sts128(sbase + OFF_STG + i * 512 + lane * 16, 0u, 0u, 0u, 0u);
        fence_async_smem();
        __syncwarp();
        if (lane == 0) {
          const uint32_t sd = first_step(cta);
          while (!flag_ready(F_CS + ((sd & 7) == T_QA ? 7 : 0) + ((sd >> 7) & 31), 32 * ep)) { __nanosleep(200); if (gtimer() - t0 > 2000000000ull) __trap(); }
          mbar_arrive(sbar + B_RDY);
        }
      }
      if (lane == 0) {
        while (!mbar_try_wait_long(sbar + B_DONE, 0)) { if (gtimer() - t0 > 2000000000ull) __trap(); }
      }
    } else if (warp >= 10 && lane == 0) {
      const int w = warp - 10;
      const uint32_t stg = sbase + OFF_STG + w * 16384;
      uint32_t cp = 0;
      while (true) {
        mbar_wait_long(sbar + B_CMD + 8 * w, cp); cp ^= 1;
        uint32_t map, col, row, f;
        lds128(sbase + OFF_CMD + w * 16, map, col, row, f);
        if (map == 0xffffu) break;
        if (map == 0xfffdu) {
          mbar_expect_tx(sbar + B_CDONE + 8 * w, 16384);
          tma_load_2d(stg, &p.maps[M_X64], sbar + B_CDONE + 8 * w, (int)col, (int)row);
          tma_load_2d(stg + 8192, &p.maps[M_X64], sbar + B_CDONE + 8 * w, (int)col + 64, (int)row);
          continue;
        }
        if (map == 0xfffeu) {
          mbar_arrive(sbar + B_CDONE + 8 * w);
          asm volatile("red.release.gpu.global.add.u32 [%0], %1;" :: "l"(&g_flags[col * 8]), "r"(row) : "memory");
          continue;
        }
        tma_store_2d(&p.maps[map], stg, (int)col, (int)row);
        tma_store_2d(&p.maps[map], stg + 8192, (int)col + 64, (int)row);
        bulk_commit();
        if (map == M_SOUT) break;
        bulk_wait_read0();
        mbar_arrive(sbar + B_CDONE + 8 * w);
        if (f != 0xffffu) { bulk_wait0(); fence_async_global(); red_release(&g_flags[f * 8]); }
      }
      bulk_wait0();
      mbar_arrive(sbar + B_DONE);
    }
  }
}

typedef CUresult (*PFN_encodeTiled)(CUtensorMap*, CUtensorMapDataType, cuuint32_t, void*, const cuuint64_t*, const cuuint64_t*,
                                    const cuuint32_t*, const cuuint32_t*, CUtensorMapInterleave, CUtensorMapSwizzle,
                                    CUtensorMapL2promotion, CUtensorMapFloatOOBfill);
static PFN_encodeTiled s_encode = nullptr;

static void map_2d(CUtensorMap* m, const void* ptr, uint64_t rows, uint64_t cols, uint32_t br, bool promo = false) {
  cuuint64_t dims[2] = {cols, rows}; cuuint64_t strides[1] = {cols * 2};
  cuuint32_t box[2] = {64, br}; cuuint32_t es[2] = {1, 1};
  s_encode(m, CU_TENSOR_MAP_DATA_TYPE_BFLOAT16, 2, (void*)ptr, dims, strides, box, es, CU_TENSOR_MAP_INTERLEAVE_NONE,
           CU_TENSOR_MAP_SWIZZLE_128B, promo ? CU_TENSOR_MAP_L2_PROMOTION_L2_256B : CU_TENSOR_MAP_L2_PROMOTION_NONE, CU_TENSOR_MAP_FLOAT_OOB_FILL_NONE);
}
static void map_3d(CUtensorMap* m, const void* ptr, uint64_t rows, uint64_t cols, uint32_t nb) {
  cuuint64_t dims[3] = {64, rows, cols / 64}; cuuint64_t strides[2] = {cols * 2, 128};
  cuuint32_t box[3] = {64, 64, nb}; cuuint32_t es[3] = {1, 1, 1};
  s_encode(m, CU_TENSOR_MAP_DATA_TYPE_BFLOAT16, 3, (void*)ptr, dims, strides, box, es, CU_TENSOR_MAP_INTERLEAVE_NONE,
           CU_TENSOR_MAP_SWIZZLE_128B, CU_TENSOR_MAP_L2_PROMOTION_NONE, CU_TENSOR_MAP_FLOAT_OOB_FILL_NONE);
}

static void build_schedule(Params& P) {
  memset(P.steps, 0, sizeof(P.steps));
  int n[NCTA] = {0};
  constexpr int NEARLY = 12;
  auto add = [&](int cta, int type, int r, int c, int aux) {
    const uint32_t prev = n[cta] > 0 ? P.steps[cta][n[cta] - 1] : 0;
    const int flush = type == T_Y && (prev & 7) == T_G && (r >= NEARLY || ((prev >> 3) & 15) < NEARLY);
    const bool second = r >= NEARLY;
    const int ha = type == T_G || type == T_S || type == T_Y || (type == T_QA && aux);
    const int hb = type == T_Z2 || type == T_QA || type == T_S || ((type == T_Z1 || type == T_G) && second);
    P.steps[cta][n[cta]++] = (uint32_t)(type | (r << 3) | (c << 7) | (flush << 12) | (aux << 13) | (ha << 24) | (hb << 25) |
                                         (type == T_S) << 26);
  };
  int nearly[16] = {0}, nparts[64] = {0};
  auto addqa = [&](int c0, int n, int q0) {
    for (int i = 0; i < n; i++) {
      const int q = q0 + i;
      add(c0 + i, T_QA, q & 15, q >> 4, q >= 172); if (q < 172) nearly[q & 15]++;
    }
  };
  auto addy = [&](int cta, int r, int c, int k0, int nk) { add(cta, T_Y, r, c, (nk / 4) | (k0 / 4) << 3 | nparts[r * 4 + c] << 6); nparts[r * 4 + c]++; };
  auto zr = [](int i) { return (i / 28) * 4 + (i & 3); };
  auto zc = [](int i) { return (i % 28) >> 2; };
  for (int i = 0; i < 112; i++) add(i, T_Z2, zr(i), zc(i), 0);
  addqa(112, 16, 0); addqa(96, 16, 32);
  for (int i = 0; i < 4; i++) { addqa(128 + i, 1, 16 + 4 * i); addqa(84 + 3 * i, 3, 17 + 4 * i); }
  for (int i = 0; i < 112; i++) { add(i, T_Z1, zr(i), zc(i), 0); add(i, T_G, zr(i), zc(i), 0); }
  addqa(112, 16, 48); addqa(112, 16, 64); addqa(128, 4, 160); addqa(128, 4, 164);
  addqa(0, 80, 80); addqa(80, 4, 168);
  addqa(80, 4, 172); addqa(0, 80, 176);
  for (int i = 0; i < 12; i++) addy(84 + i, i % 3, i / 3, 0, 28);
  for (int i = 0; i < 32; i++) addy(96 + i, 3 + (i >> 4) * 4 + (i & 3), (i >> 2) & 3, 0, 28);
  for (int k = 0; k < 2; k++) for (int i = 0; i < 4; i++) addy(128 + i, 11 + k, i, 0, 28);
  for (int i = 0; i < 12; i++) {
    const int r = 13 + i % 3, c = i / 3;
    addy(84 + i, r, c, 0, 8); addy(96 + i, r, c, 8, 8);
    if (r == 13) { addy(128 + c, r, c, 16, 8); addy(108 + c, r, c, 24, 4); }
    else { const int k = (r - 14) * 4 + c; addy(112 + k, r, c, 16, 8); addy(120 + k, r, c, 24, 4); }
  }
  for (int i = 0; i < 128; i++) {
    const int r = (i >> 5) * 4 + (i & 3), c = (i >> 2) & 7;
    add(i, T_S, r, c, nearly[r] | nparts[r * 4 + (c >> 1)] << 5);
  }
}

extern "C" void kernel_launch(void* const* d_in, const int* in_sizes, int n_in, void* d_out, int out_size) {
  (void)in_sizes; (void)n_in; (void)out_size;
  static Params P;
  static void *xn, *z2n, *u, *o, *gate;
  if (!s_encode) {
    void* fn = nullptr; cudaDriverEntryPointQueryResult qr;
    cudaGetDriverEntryPoint("cuTensorMapEncodeTiled", &fn, cudaEnableDefault, &qr);
    s_encode = (PFN_encodeTiled)fn;
    cudaGetSymbolAddress(&xn, g_xn); cudaGetSymbolAddress(&z2n, g_z2n); cudaGetSymbolAddress(&u, g_u);
    cudaGetSymbolAddress(&o, g_o); cudaGetSymbolAddress(&gate, g_y);
    cudaFuncSetAttribute(mega_kernel, cudaFuncAttributeMaxDynamicSharedMemorySize, SMEM_BYTES);
    build_schedule(P);
  }
  const void *x = d_in[0], *kc = d_in[1], *vc = d_in[2], *wq = d_in[3], *wo = d_in[4];
  const void *w_in = d_in[6], *w_sp = d_in[7], *b_sp = d_in[8], *w_out = d_in[9];
  map_2d(&P.maps[M_XN], xn, SEQ, DM, 128);
  map_2d(&P.maps[M_WSP], w_sp, SEQ, SEQ, 128, true);
  map_2d(&P.maps[M_U], u, SEQ, FH, 128);
  map_2d(&P.maps[M_O], o, SEQ, HQD, 128);
  map_2d(&P.maps[M_X], x, SEQ, DM, 128, true);
  map_2d(&P.maps[M_Y], gate, 4 * SEQ, DM, 128);
  map_2d(&P.maps[M_K], kc, 4 * SK, 128, 128);
  map_2d(&P.maps[M_V], vc, 4 * SK, 128, 128);
  map_3d(&P.maps[M_WQ], wq, DM, HQD, 4);
  map_3d(&P.maps[M_WIN], w_in, DM, 2 * FH, 4);
  map_3d(&P.maps[M_Z2N], z2n, SEQ, FH, 4);
  map_3d(&P.maps[M_WOUT], w_out, FH, DM, 4);
  map_3d(&P.maps[M_WO2], wo, HQD, DM, 2);
  map_2d(&P.maps[M_SZ2N], z2n, SEQ, FH, 64);
  map_2d(&P.maps[M_SU], u, SEQ, FH, 64);
  map_2d(&P.maps[M_SO], o, SEQ, HQD, 64);
  map_2d(&P.maps[M_SY], gate, 4 * SEQ, DM, 64);
  map_2d(&P.maps[M_SOUT], d_out, SEQ, DM, 64);
  map_2d(&P.maps[M_X64], x, SEQ, DM, 64);
  P.x = (const bf16*)x;
  P.b_sp = (const bf16*)b_sp;
  P.never = 0xFFC12345u;
  mega_kernel<<<NCTA, 384, SMEM_BYTES>>>(P);
}
```
